```python
import torch

def _softmax(x, axis=-1):
    return torch.softmax(x, dim=axis)

def _gelu(x):
    return torch.nn.functional.gelu(x, approximate='tanh')

def _silu(x):
    return torch.nn.functional.silu(x)

def _sigmoid(x):
    return torch.sigmoid(x)

def _layernorm(x, axis=-1, eps=1e-05):
    m = x.mean(dim=axis, keepdim=True)
    v = x.var(dim=axis, keepdim=True, unbiased=False)
    return (x - m) / torch.sqrt(v + eps)

def _scatter_add(tgt, idx, src, axis=0):
    return tgt.clone().index_add_(axis, idx, src)

def _segment_sum(src, seg, n):
    out = torch.zeros((n,) + src.shape[1:], dtype=src.dtype)
    return out.index_add_(0, seg, src)

def _pad(x, pw):
    flat = tuple((v for pair in reversed(pw) for v in pair))
    return torch.nn.functional.pad(x, flat)
kernel_name = 'parallel_sum__memory_aug_recurrent_mem_tr__glu_gated_bilinear__prompt'

def setup_inputs():

    _w = lambda a: (lambda t: t.to(torch.bfloat16) if t.is_floating_point() else t)(torch.as_tensor(a))

    def _A_setup():
        B, S, Dm = (1, 2048, 640)
        H, Dh = (32, 192)
        M, seg = (8, 32)
        seg = min(seg, S)
        S = S // seg * seg
        return {'x': _w((lambda *s: torch.randn(*s, dtype=torch.bfloat16) * 0.05)(B, S, Dm)), 'mem0': _w((lambda *s: torch.randn(*s, dtype=torch.bfloat16) * 0.2)(B, M, Dm)), 'Wq': _w((lambda *s: torch.randn(*s, dtype=torch.bfloat16) * 1.6)(Dm, H, Dh) * Dm ** (-0.5)), 'Wk': _w((lambda *s: torch.randn(*s, dtype=torch.bfloat16) * 1.6)(Dm, H, Dh) * Dm ** (-0.5)), 'Wv': _w((lambda *s: torch.randn(*s, dtype=torch.bfloat16) * 0.2)(Dm, H, Dh) * Dm ** (-0.5)), 'Wo': _w((lambda *s: torch.randn(*s, dtype=torch.bfloat16) * 0.2)(H, Dh, Dm) * (H * Dh) ** (-0.5)), 'seg_len': seg}
    _A_in = _A_setup()

    def _B_setup():
        B, S, D, F = (1, 2048, 640, 1536)
        return {'x': _w((lambda *s: torch.randn(*s, dtype=torch.bfloat16) * 0.05)(B, S, D)), 'w_gate': _w((lambda *s: torch.randn(*s, dtype=torch.bfloat16) * 0.2)(D, F) * D ** (-0.5)), 'w_up': _w((lambda *s: torch.randn(*s, dtype=torch.bfloat16) * 0.2)(D, F) * D ** (-0.5)), 'w_down': _w((lambda *s: torch.randn(*s, dtype=torch.bfloat16) * 0.2)(F, D) * F ** (-0.5))}
    _B_in = _B_setup()
    return {'A_x': _A_in['x'], 'A_mem0': _A_in['mem0'], 'A_Wq': _A_in['Wq'], 'A_Wk': _A_in['Wk'], 'A_Wv': _A_in['Wv'], 'A_Wo': _A_in['Wo'], 'A_seg_len': _A_in['seg_len'], 'B_x': _B_in['x'], 'B_w_gate': _B_in['w_gate'], 'B_w_up': _B_in['w_up'], 'B_w_down': _B_in['w_down']}

def reference(A_x, A_mem0, A_Wq, A_Wk, A_Wv, A_Wo, A_seg_len, B_x, B_w_gate, B_w_up, B_w_down):

    def _A_ref(x, mem0, Wq, Wk, Wv, Wo, seg_len):
        B, S, Dm = x.shape
        H, Dh = (Wq.shape[1], Wq.shape[2])
        M = mem0.shape[1]
        scale = Dh ** (-0.5)
        n_seg = S // seg_len
        L = M + seg_len
        idx = torch.arange(L)
        mask = (idx[:, None] < M) | (idx[:, None] >= idx[None, :])
        mem = mem0
        outs = []
        for s in range(n_seg):
            xs = x[:, s * seg_len:(s + 1) * seg_len, :].clone()
            h = torch.concatenate([mem, xs], axis=1)
            q = torch.einsum('btd,dhe->bhte', h, Wq)
            k = torch.einsum('btd,dhe->bhte', h, Wk)
            v = torch.einsum('btd,dhe->bhte', h, Wv)
            scores = torch.einsum('bhqe,bhke->bhqk', q, k) * scale
            scores = torch.where(mask[None, None], scores, -1000000000.0)
            p = _softmax(scores, axis=-1)
            o = torch.einsum('bhqk,bhke->bhqe', p, v)
            o = torch.einsum('bhte,hed->btd', o, Wo)
            mem = o[:, :M, :].clone()
            outs.append(o[:, M:, :])
        return torch.concatenate(outs, axis=1)

    def _B_ref(x, w_gate, w_up, w_down):
        g = torch.einsum('bsd,df->bsf', x, w_gate)
        u = torch.einsum('bsd,df->bsf', x, w_up)
        h = g * u
        return torch.einsum('bsf,fd->bsd', h, w_down)
    x = A_x
    xn = _layernorm(x, axis=-1)
    return x + _A_ref(xn, A_mem0, A_Wq, A_Wk, A_Wv, A_Wo, A_seg_len) + _B_ref(xn, B_w_gate, B_w_up, B_w_down)
```

```cpp
#include <cuda_runtime.h>
#include <cuda_bf16.h>
#include <cuda.h>
#include <stdint.h>

typedef __nv_bfloat16 bf16;

constexpr int SEQ = 2048, DM = 640, HD = 6144, FF = 1536, NSEG = 64;
constexpr int ACC_CHUNKS = 1792;

__device__ bf16 g_xn[SEQ * DM];
__device__ bf16 g_oT[NSEG * HD * 32];
__device__ bf16 g_h[SEQ * FF];
__device__ float4 g_acc[NSEG * ACC_CHUNKS];
#define PROF(who, slot) do {} while (0)

__device__ __forceinline__ uint32_t smem_u32(const void* p) { return (uint32_t)__cvta_generic_to_shared(p); }
__device__ __forceinline__ uint32_t mapa(uint32_t a, uint32_t r) { uint32_t o; asm("mapa.shared::cluster.u32 %0, %1, %2;" : "=r"(o) : "r"(a), "r"(r)); return o; }
__device__ __forceinline__ void mbar_init(uint32_t b, int c) { asm volatile("mbarrier.init.shared::cta.b64 [%0], %1;" :: "r"(b), "r"(c) : "memory"); }
__device__ __forceinline__ void mbar_expect(uint32_t b, uint32_t bytes) { asm volatile("mbarrier.arrive.expect_tx.shared::cta.b64 _, [%0], %1;" :: "r"(b), "r"(bytes) : "memory"); }
__device__ __forceinline__ void mbar_arrive(uint32_t b) { asm volatile("mbarrier.arrive.shared::cta.b64 _, [%0];" :: "r"(b) : "memory"); }
__device__ __forceinline__ bool mbar_try(uint32_t b, uint32_t ph) {
  uint32_t ok;
  asm volatile("{\n.reg .pred p;\nmbarrier.try_wait.parity.shared::cta.b64 p, [%1], %2;\nselp.u32 %0, 1, 0, p;\n}" : "=r"(ok) : "r"(b), "r"(ph) : "memory");
  return ok;
}
__device__ __forceinline__ bool mbar_try_cl(uint32_t b, uint32_t ph) {
  uint32_t ok;
  asm volatile("{\n.reg .pred p;\nmbarrier.try_wait.parity.acquire.cluster.shared::cta.b64 p, [%1], %2;\nselp.u32 %0, 1, 0, p;\n}" : "=r"(ok) : "r"(b), "r"(ph) : "memory");
  return ok;
}
constexpr int SPIN_LIMIT = 1 << 22;
__device__ __forceinline__ void mbar_wait(uint32_t b, uint32_t ph) {
  if (mbar_try(b, ph)) return;
  int n = 0;
  while (!mbar_try(b, ph)) { if (++n > SPIN_LIMIT) __trap(); }
}
__device__ __forceinline__ void mbar_wait_cl(uint32_t b, uint32_t ph) {
  if (mbar_try_cl(b, ph)) return;
  int n = 0;
  while (!mbar_try_cl(b, ph)) { if (++n > SPIN_LIMIT) __trap(); }
}
__device__ __forceinline__ void bar_sync(int id, int n) { asm volatile("bar.sync %0, %1;" :: "r"(id), "r"(n) : "memory"); }
__device__ __forceinline__ void bar_arrive(int id, int n) { asm volatile("bar.arrive %0, %1;" :: "r"(id), "r"(n) : "memory"); }
__device__ __forceinline__ void fence_async() { asm volatile("fence.proxy.async.shared::cta;" ::: "memory"); }
__device__ __forceinline__ void cluster_sync() { asm volatile("barrier.cluster.arrive.release.aligned;\nbarrier.cluster.wait.acquire.aligned;" ::: "memory"); }
__device__ __forceinline__ void tma2d(uint32_t dst, const CUtensorMap* m, int c0, int c1, uint32_t bar) {
  asm volatile("cp.async.bulk.tensor.2d.shared::cluster.global.mbarrier::complete_tx::bytes [%0], [%1, {%3, %4}], [%2];"
               :: "r"(dst), "l"(m), "r"(bar), "r"(c0), "r"(c1) : "memory");
}
__device__ __forceinline__ void tma3d(uint32_t dst, const CUtensorMap* m, int c0, int c1, int c2, uint32_t bar) {
  asm volatile("cp.async.bulk.tensor.3d.shared::cluster.global.mbarrier::complete_tx::bytes [%0], [%1, {%3, %4, %5}], [%2];"
               :: "r"(dst), "l"(m), "r"(bar), "r"(c0), "r"(c1), "r"(c2) : "memory");
}
__device__ __forceinline__ void st_async2(uint32_t a, uint32_t x, uint32_t y, uint32_t mb) {
  asm volatile("st.async.weak.shared::cluster.mbarrier::complete_tx::bytes.v2.b32 [%0], {%1,%2}, [%3];" :: "r"(a), "r"(x), "r"(y), "r"(mb) : "memory");
}
__device__ __forceinline__ void st_async4(uint32_t a, uint32_t x, uint32_t y, uint32_t z, uint32_t w, uint32_t mb) {
  asm volatile("st.async.weak.shared::cluster.mbarrier::complete_tx::bytes.v4.b32 [%0], {%1,%2,%3,%4}, [%5];" :: "r"(a), "r"(x), "r"(y), "r"(z), "r"(w), "r"(mb) : "memory");
}
__device__ __forceinline__ void ldsm4(uint32_t& r0, uint32_t& r1, uint32_t& r2, uint32_t& r3, uint32_t a) {
  asm volatile("ldmatrix.sync.aligned.m8n8.x4.shared.b16 {%0,%1,%2,%3}, [%4];" : "=r"(r0), "=r"(r1), "=r"(r2), "=r"(r3) : "r"(a) : "memory");
}
__device__ __forceinline__ void ldsm4t(uint32_t& r0, uint32_t& r1, uint32_t& r2, uint32_t& r3, uint32_t a) {
  asm volatile("ldmatrix.sync.aligned.m8n8.x4.trans.shared.b16 {%0,%1,%2,%3}, [%4];" : "=r"(r0), "=r"(r1), "=r"(r2), "=r"(r3) : "r"(a) : "memory");
}
__device__ __forceinline__ void stsm4t(uint32_t a, uint32_t r0, uint32_t r1, uint32_t r2, uint32_t r3) {
  asm volatile("stmatrix.sync.aligned.m8n8.x4.trans.shared.b16 [%0], {%1,%2,%3,%4};" :: "r"(a), "r"(r0), "r"(r1), "r"(r2), "r"(r3) : "memory");
}
__device__ __forceinline__ void stsm2t(uint32_t a, uint32_t r0, uint32_t r1) {
  asm volatile("stmatrix.sync.aligned.m8n8.x2.trans.shared.b16 [%0], {%1,%2};" :: "r"(a), "r"(r0), "r"(r1) : "memory");
}
__device__ __forceinline__ void mma16816(float* d, uint32_t a0, uint32_t a1, uint32_t a2, uint32_t a3, uint32_t b0, uint32_t b1) {
  asm volatile("mma.sync.aligned.m16n8k16.row.col.f32.bf16.bf16.f32 {%0,%1,%2,%3}, {%4,%5,%6,%7}, {%8,%9}, {%0,%1,%2,%3};"
               : "+f"(d[0]), "+f"(d[1]), "+f"(d[2]), "+f"(d[3]) : "r"(a0), "r"(a1), "r"(a2), "r"(a3), "r"(b0), "r"(b1));
}
__device__ __forceinline__ uint32_t pack2(float lo, float hi) { uint32_t r; asm("cvt.rn.bf16x2.f32 %0, %1, %2;" : "=r"(r) : "f"(hi), "f"(lo)); return r; }
__device__ __forceinline__ float2 lds2f(uint32_t a) { float2 v; asm volatile("ld.shared.v2.f32 {%0,%1}, [%2];" : "=f"(v.x), "=f"(v.y) : "r"(a) : "memory"); return v; }
__device__ __forceinline__ float4 lds4f(uint32_t a) { float4 v; asm volatile("ld.shared.v4.f32 {%0,%1,%2,%3}, [%4];" : "=f"(v.x), "=f"(v.y), "=f"(v.z), "=f"(v.w) : "r"(a) : "memory"); return v; }
__device__ __forceinline__ uint4 lds4u(uint32_t a) { uint4 v; asm volatile("ld.shared.v4.u32 {%0,%1,%2,%3}, [%4];" : "=r"(v.x), "=r"(v.y), "=r"(v.z), "=r"(v.w) : "r"(a) : "memory"); return v; }
__device__ __forceinline__ float lds1f(uint32_t a) { float v; asm volatile("ld.shared.f32 %0, [%1];" : "=f"(v) : "r"(a) : "memory"); return v; }
__device__ __forceinline__ void sts4f(uint32_t a, float x, float y, float z, float w) { asm volatile("st.shared.v4.f32 [%0], {%1,%2,%3,%4};" :: "r"(a), "f"(x), "f"(y), "f"(z), "f"(w) : "memory"); }
__device__ __forceinline__ void sts2f(uint32_t a, float x, float y) { asm volatile("st.shared.v2.f32 [%0], {%1,%2};" :: "r"(a), "f"(x), "f"(y) : "memory"); }
__device__ __forceinline__ void sts1f(uint32_t a, float x) { asm volatile("st.shared.f32 [%0], %1;" :: "r"(a), "f"(x) : "memory"); }
__device__ __forceinline__ void sts1u(uint32_t a, uint32_t x) { asm volatile("st.shared.u32 [%0], %1;" :: "r"(a), "r"(x) : "memory"); }
__device__ __forceinline__ void sts4u(uint32_t a, uint4 v) { asm volatile("st.shared.v4.u32 [%0], {%1,%2,%3,%4};" :: "r"(a), "r"(v.x), "r"(v.y), "r"(v.z), "r"(v.w) : "memory"); }
__device__ __forceinline__ float4 ld_relaxed4(const float4* p) {
  float4 r; asm volatile("ld.relaxed.gpu.global.v4.f32 {%0,%1,%2,%3}, [%4];" : "=f"(r.x), "=f"(r.y), "=f"(r.z), "=f"(r.w) : "l"(p) : "memory"); return r;
}
__device__ __forceinline__ void red4(float4* p, float a, float b, float c, float d) {
  asm volatile("red.relaxed.gpu.global.add.v4.f32 [%0], {%1,%2,%3,%4};" :: "l"(p), "f"(a), "f"(b), "f"(c), "f"(d) : "memory");
}
__device__ __forceinline__ uint64_t mkdesc(uint32_t addr, uint32_t lbo, uint32_t sbo, uint32_t swz) {
  return (uint64_t)((addr & 0x3FFFF) >> 4) | ((uint64_t)(lbo >> 4) << 16) | ((uint64_t)(sbo >> 4) << 32) | ((uint64_t)swz << 62);
}
#define WG_FENCE() asm volatile("wgmma.fence.sync.aligned;" ::: "memory")
#define WG_COMMIT() asm volatile("wgmma.commit_group.sync.aligned;" ::: "memory")
#define WG_WAIT(n) asm volatile("wgmma.wait_group.sync.aligned %0;" :: "n"(n) : "memory")
#define OPAQUE64(x) asm volatile("" : "+l"(x))

#define F4(d, i) "+f"(d[i]), "+f"(d[i + 1]), "+f"(d[i + 2]), "+f"(d[i + 3])
#define F16(d, i) F4(d, i), F4(d, i + 4), F4(d, i + 8), F4(d, i + 12)
template <int ACC>
__device__ __forceinline__ void wg_rs32(float* d, uint32_t a0, uint32_t a1, uint32_t a2, uint32_t a3, uint64_t b) {
  asm volatile("wgmma.mma_async.sync.aligned.m64n32k16.f32.bf16.bf16 {%0,%1,%2,%3,%4,%5,%6,%7,%8,%9,%10,%11,%12,%13,%14,%15}, {%16,%17,%18,%19}, %20, %21, 1, 1, 0;"
               : F16(d, 0) : "r"(a0), "r"(a1), "r"(a2), "r"(a3), "l"(b), "n"(ACC));
}
template <int ACC>
__device__ __forceinline__ void wg_rs40(float* d, uint32_t a0, uint32_t a1, uint32_t a2, uint32_t a3, uint64_t b) {
  asm volatile("wgmma.mma_async.sync.aligned.m64n40k16.f32.bf16.bf16 {%0,%1,%2,%3,%4,%5,%6,%7,%8,%9,%10,%11,%12,%13,%14,%15,%16,%17,%18,%19}, {%20,%21,%22,%23}, %24, %25, 1, 1, 0;"
               : F16(d, 0), F4(d, 16) : "r"(a0), "r"(a1), "r"(a2), "r"(a3), "l"(b), "n"(ACC));
}
template <int ACC, int TA>
__device__ __forceinline__ void wg_ss40(float* d, uint64_t a, uint64_t b) {
  asm volatile("wgmma.mma_async.sync.aligned.m64n40k16.f32.bf16.bf16 {%0,%1,%2,%3,%4,%5,%6,%7,%8,%9,%10,%11,%12,%13,%14,%15,%16,%17,%18,%19}, %20, %21, %22, 1, 1, %23, 0;"
               : F16(d, 0), F4(d, 16) : "l"(a), "l"(b), "n"(ACC), "n"(TA));
}
template <int TA>
__device__ __forceinline__ void wg_ss128(float* d, uint64_t a, uint64_t b) {
  asm volatile("wgmma.mma_async.sync.aligned.m64n128k16.f32.bf16.bf16 {"
               "%0,%1,%2,%3,%4,%5,%6,%7,%8,%9,%10,%11,%12,%13,%14,%15,%16,%17,%18,%19,%20,%21,%22,%23,%24,%25,%26,%27,%28,%29,%30,%31,"
               "%32,%33,%34,%35,%36,%37,%38,%39,%40,%41,%42,%43,%44,%45,%46,%47,%48,%49,%50,%51,%52,%53,%54,%55,%56,%57,%58,%59,%60,%61,%62,%63"
               "}, %64, %65, 1, 1, 1, %66, 1;"
               : F16(d, 0), F16(d, 16), F16(d, 32), F16(d, 48) : "l"(a), "l"(b), "n"(TA));
}

__device__ __forceinline__ float bfr(float x) { return __bfloat162float(__float2bfloat16_rn(x)); }
__global__ void __launch_bounds__(256) ln_kernel(const bf16* __restrict__ x) {
  const int lane = threadIdx.x & 31, row = blockIdx.x * 8 + (threadIdx.x >> 5);
  {
    int i = blockIdx.x * 256 + threadIdx.x;
    for (; i < NSEG * ACC_CHUNKS; i += 256 * 256) g_acc[i] = make_float4(0.f, 0.f, 0.f, 0.f);
  }
  const uint2* src = reinterpret_cast<const uint2*>(x + (size_t)row * DM);
  float v[20];
#pragma unroll
  for (int i = 0; i < 5; i++) {
    uint2 u = __ldg(src + i * 32 + lane);
    v[4 * i + 0] = __uint_as_float(u.x << 16); v[4 * i + 1] = __uint_as_float(u.x & 0xffff0000u);
    v[4 * i + 2] = __uint_as_float(u.y << 16); v[4 * i + 3] = __uint_as_float(u.y & 0xffff0000u);
  }
  float s = 0.f;
#pragma unroll
  for (int i = 0; i < 20; i++) s += v[i];
#pragma unroll
  for (int o = 16; o; o >>= 1) s += __shfl_xor_sync(~0u, s, o);
  const float mean = s * (1.0f / DM);
  float q = 0.f;
#pragma unroll
  for (int i = 0; i < 20; i++) { float d = v[i] - mean; q += d * d; }
#pragma unroll
  for (int o = 16; o; o >>= 1) q += __shfl_xor_sync(~0u, q, o);
  const float mb = bfr(mean), sd = bfr(sqrtf(bfr(bfr(q * (1.0f / DM)) + 1e-5f)));
  uint2* dst = reinterpret_cast<uint2*>(g_xn + (size_t)row * DM);
#pragma unroll
  for (int i = 0; i < 5; i++) {
    uint2 u;
    u.x = pack2(bfr(v[4 * i + 0] - mb) / sd, bfr(v[4 * i + 1] - mb) / sd);
    u.y = pack2(bfr(v[4 * i + 2] - mb) / sd, bfr(v[4 * i + 3] - mb) / sd);
    dst[i * 32 + lane] = u;
  }
}

namespace ck {
constexpr int CL = 6, NCL = 16, NRF = 5, NSS = 40 - NRF;
constexpr uint32_t OFF_H = 0, OFF_WV = 51200, OFF_WO = OFF_WV + NSS * 2048, OFF_Q = OFF_WO + 86016, OFF_K = OFF_Q + 5120,
                   OFF_OG = OFF_K + 5120, OFF_RA = OFF_OG + 6144, OFF_P = OFF_RA + 3840, OFF_BAR = OFF_P + 3072, SMEM = OFF_BAR + 128;
constexpr uint32_t B_X = 0, B_A = 8, B_T = 16, B_W = 24, B_WR = 32, B_B = 40;
enum { NB_M = 1, NB_QK = 2, NB_K2 = 3, NB_V = 4, NB_TS = 5, NB_P = 6, NB_R = 7   };
static_assert(SMEM <= 232448, "smem");
static_assert(OFF_WO % 1024 == 0 && OFF_Q % 1024 == 0, "align");
}
__device__ __forceinline__ uint32_t opq(uint32_t x) { asm volatile("" : "+r"(x)); return x; }

__device__ __forceinline__ uint32_t memrow_addr(uint32_t sb, uint32_t col0, uint32_t m) {
  return sb + ck::OFF_H + (col0 >> 6) * 5120 + 4096 + m * 128 + ((((col0 >> 3) & 7) ^ m) << 4);
}
struct MemLoad { float4 c[4]; };
__device__ __forceinline__ void memload_issue(MemLoad& m, int s, uint32_t tid) {
  const float4* p = g_acc + (s * ACC_CHUNKS + (tid >> 5) * 128 + (tid & 31));
#pragma unroll
  for (int q = 0; q < 4; q++) m.c[q] = ld_relaxed4(p + q * 32);
}
__device__ __forceinline__ void memload_finish(MemLoad& m, int s, uint32_t tid, uint32_t sb) {
  const uint32_t lane = tid & 31, warp = tid >> 5;
  const uint32_t a4 = memrow_addr(sb, warp * 48 + (lane >> 3) * 8, lane & 7);
  const uint32_t a2 = memrow_addr(sb, warp * 48 + 32 + ((lane >> 3) & 1) * 8, lane & 7);
  int n = 0;
  while (true) {
    bool ok = m.c[0].w == (float)ck::NCL && m.c[1].w == (float)ck::NCL && m.c[2].w == (float)ck::NCL && m.c[3].w == (float)ck::NCL;
    if (__all_sync(~0u, ok)) break;
    if (++n > SPIN_LIMIT) __trap();
    memload_issue(m, s, tid);
  }
  stsm4t(a4, pack2(m.c[0].x, m.c[0].y), pack2(m.c[0].z, m.c[1].x), pack2(m.c[1].y, m.c[1].z), pack2(m.c[2].x, m.c[2].y));
  stsm2t(a2, pack2(m.c[2].z, m.c[3].x), pack2(m.c[3].y, m.c[3].z));
}
#define HOFF(k) ((uint64_t)((((k) >> 2) * 5120 + ((k) & 3) * 32) >> 4))

template <bool LOADS>
__device__ __forceinline__ void token_qk(const uint32_t* a, int s, uint32_t sb, uint32_t tid0) {
  using namespace ck;
  const uint32_t bar = sb + OFF_BAR;
  float d[16];
  MemLoad ml;
  mbar_wait(bar + B_X, (s + 1) & 1);
  if (LOADS) PROF(tid0 >> 7, 4);
  uint64_t db = mkdesc(sb + OFF_H, 16, 1024, 1);
  OPAQUE64(db);
  WG_FENCE();
  wg_rs32<0>(d, a[0], a[1], a[2], a[3], db);
#pragma unroll
  for (int k = 1; k < 20; k++) wg_rs32<1>(d, a[4 * k], a[4 * k + 1], a[4 * k + 2], a[4 * k + 3], db + HOFF(k));
  if (LOADS) memload_issue(ml, s, opq(tid0));
#pragma unroll
  for (int k = 20; k < 40; k++) wg_rs32<1>(d, a[4 * k], a[4 * k + 1], a[4 * k + 2], a[4 * k + 3], db + HOFF(k));
  WG_COMMIT();
  const uint32_t tid = opq(tid0), lane = tid & 31, wg = tid >> 7, w4 = (tid >> 5) & 3;
  const uint32_t mat = lane >> 3, i = lane & 7, h = mat & 1, j0 = mat >> 1;
  const uint32_t n0 = wg == 0 ? 8 * (i >> 1) + 2 * j0 + (i & 1) : 8 * j0 + i;
  const uint32_t n1 = wg == 0 ? n0 + 4 : n0 + 16;
  const uint32_t qk = sb + OFF_Q + wg * 5120;
  const uint32_t ep0 = qk + n0 * 128 + (((2 * w4 + h) ^ (n0 & 7)) << 4);
  const uint32_t ep1 = qk + n1 * 128 + (((2 * w4 + h) ^ (n1 & 7)) << 4);
  WG_WAIT(0);
  if (LOADS) PROF(tid0 >> 7, 5);
  bar_sync(NB_TS, 384);
  stsm4t(ep0, pack2(d[0], d[1]), pack2(d[2], d[3]), pack2(d[4], d[5]), pack2(d[6], d[7]));
  stsm4t(ep1, pack2(d[8], d[9]), pack2(d[10], d[11]), pack2(d[12], d[13]), pack2(d[14], d[15]));
  if (LOADS) PROF(tid0 >> 7, 6);
  if (LOADS) memload_finish(ml, s, opq(tid0), sb);
  fence_async();
  if (LOADS) PROF(tid0 >> 7, 7);
}

__global__ void __launch_bounds__(384, 1)
chain_kernel(const __grid_constant__ CUtensorMap tm_x, const __grid_constant__ CUtensorMap tm_wv, const __grid_constant__ CUtensorMap tm_wo,
             const bf16* __restrict__ Wq, const bf16* __restrict__ Wk, const bf16* __restrict__ mem0) {
  using namespace ck;
  extern __shared__ __align__(1024) unsigned char smem[];
  const uint32_t sb = smem_u32(smem);
  const uint32_t tid0 = threadIdx.x;
  const int rank = blockIdx.x % CL, cluster = blockIdx.x / CL;
  const int hb = (rank / 3) * 3, j3 = rank % 3;
  const uint32_t bar = sb + OFF_BAR;

  if (tid0 == 0) {
    const int ntile = rank < 4 ? 7 : 6;
    mbar_init(bar + B_X, 1); mbar_init(bar + B_A, 1); mbar_init(bar + B_T, 1); mbar_init(bar + B_W, 1); mbar_init(bar + B_WR, 1);
    for (int i = 0; i < CL; i++) mbar_init(bar + B_B + 8 * i, 1);
    asm volatile("fence.mbarrier_init.release.cluster;" ::: "memory");
    mbar_expect(bar + B_A, 3 * 1280); mbar_expect(bar + B_T, 2 * 5120);
    for (int i = 0; i < CL; i++) mbar_expect(bar + B_B + 8 * i, 1024);
    mbar_expect(bar + B_X, 40960);
    for (int c = 0; c < 10; c++) tma2d(sb + OFF_H + c * 5120, &tm_x, c * 64, 0, bar + B_X);
    mbar_expect(bar + B_WR, NRF * 2048);
    tma2d(sb + OFF_Q, &tm_wv, blockIdx.x * 64, NSS * 16, bar + B_WR);
    mbar_expect(bar + B_W, NSS * 2048 + ntile * 12288);
    for (int i = 0; i < NSS / 5; i++) tma2d(sb + OFF_WV + i * 10240, &tm_wv, blockIdx.x * 64, i * 80, bar + B_W);
    for (int i = 0; i < ntile; i++) {
      const int col = i < 6 ? rank * 96 + i * 16 : 576 + rank * 16;
      tma2d(sb + OFF_WO + i * 12288, &tm_wo, col, cluster * 384, bar + B_W);
      tma2d(sb + OFF_WO + i * 12288 + 6144, &tm_wo, col, cluster * 384 + 192, bar + B_W);
    }
  }
  for (int i = tid0; i < 640; i += 384) {
    const int m = i / 80, c = i % 80;
    sts4u(memrow_addr(sb, c * 8, m), __ldg(reinterpret_cast<const uint4*>(mem0) + i));
  }
  if (tid0 < 128) sts1u(sb + OFF_P + (tid0 >> 5) * 768 + 640 + (tid0 & 31) * 4, 0u);
  fence_async();
  __syncthreads();
  cluster_sync();

  if (tid0 < 256) {
    asm volatile("setmaxnreg.inc.sync.aligned.u32 208;");
    uint32_t a[160];
    {
      const uint32_t lane = tid0 & 31;
      const uint32_t* W = reinterpret_cast<const uint32_t*>((tid0 < 128 ? Wq : Wk) + (size_t)(2 * (lane & 3)) * HD + blockIdx.x * 64 + ((tid0 >> 5) & 3) * 16 + 2 * (lane >> 2));
#pragma unroll
      for (int k = 0; k < 40; k++) {
        a[4 * k + 0] = __ldg(W + (size_t)(16 * k + 0) * (HD / 2));
        a[4 * k + 1] = __ldg(W + (size_t)(16 * k + 1) * (HD / 2));
        a[4 * k + 2] = __ldg(W + (size_t)(16 * k + 8) * (HD / 2));
        a[4 * k + 3] = __ldg(W + (size_t)(16 * k + 9) * (HD / 2));
      }
#pragma unroll
      for (int k = 0; k < 80; k++) {
        const uint32_t w0 = a[2 * k], w1 = a[2 * k + 1];
        a[2 * k] = __byte_perm(w0, w1, 0x5410);
        a[2 * k + 1] = __byte_perm(w0, w1, 0x7632);
      }
    }
    token_qk<false>(a, -1, sb, tid0);
    mbar_wait(bar + B_W, 0);

    for (int s = 0;; s++) {
      {
        const uint32_t tid = opq(tid0), l7 = tid & 7, l3 = (tid >> 3) & 3;
        const uint32_t mb = sb + OFF_H + 4096 + l7 * 128;
        const uint32_t x0 = mb + ((l3 ^ l7) << 4), x1 = mb + (((4 + l3) ^ l7) << 4);
        const uint32_t qst = sb + OFF_Q + (tid >> 7) * 5120 + (32 + l7) * 128 + (((2 * ((tid >> 5) & 3) + (l3 & 1)) ^ l7) << 4);
        float c[16];
#pragma unroll
        for (int i = 0; i < 16; i++) c[i] = 0.f;
        bar_sync(NB_M, 384);
        PROF(tid0 >> 7, 0);
#pragma unroll
        for (int k = 0; k < 40; k += 2) {
          uint32_t b0, b1, b2, b3;
          ldsm4(b0, b1, b2, b3, ((k & 2) ? x1 : x0) + (k >> 2) * 5120);
          float* d = c + ((k & 2) ? 8 : 0);
          mma16816(d, a[4 * k], a[4 * k + 1], a[4 * k + 2], a[4 * k + 3], b0, b1);
          mma16816(d + 4, a[4 * k + 4], a[4 * k + 5], a[4 * k + 6], a[4 * k + 7], b2, b3);
        }
#pragma unroll
        for (int i = 0; i < 4; i++) c[i] = (c[i] + c[4 + i]) + (c[8 + i] + c[12 + i]);
        stsm2t(qst, pack2(c[0], c[1]), pack2(c[2], c[3]));
        fence_async();
        PROF(tid0 >> 7, 1);
        bar_arrive(NB_K2, 384);
      }
      if (s == NSEG - 1) break;
      const uint32_t tid = opq(tid0), lane = tid & 31, warp = tid >> 5, l7 = tid & 7, l3 = lane >> 3;
      bar_sync(NB_QK, 256);
      if (warp < 5) {
        uint32_t qa[8], kb[8];
        const uint32_t qr = sb + OFF_Q + (32 + l7) * 128, kr = sb + OFF_K + (8 * warp + l7) * 128;
        ldsm4(qa[0], qa[1], qa[2], qa[3], qr + ((l3 ^ l7) << 4));
        ldsm4(kb[0], kb[1], kb[2], kb[3], kr + ((l3 ^ l7) << 4));
        ldsm4(qa[4], qa[5], qa[6], qa[7], qr + (((4 + l3) ^ l7) << 4));
        ldsm4(kb[4], kb[5], kb[6], kb[7], kr + (((4 + l3) ^ l7) << 4));
        float s0[4] = {0.f, 0.f, 0.f, 0.f}, s1[4] = {0.f, 0.f, 0.f, 0.f};
        mma16816(s0, qa[0], 0u, qa[1], 0u, kb[0], kb[1]);
        mma16816(s1, qa[2], 0u, qa[3], 0u, kb[2], kb[3]);
        mma16816(s0, qa[4], 0u, qa[5], 0u, kb[4], kb[5]);
        mma16816(s1, qa[6], 0u, qa[7], 0u, kb[6], kb[7]);
        const uint32_t x = __float_as_uint(s0[0] + s1[0]), y = __float_as_uint(s0[1] + s1[1]);
        const uint32_t off = OFF_RA + j3 * 1280 + tid * 8;
#pragma unroll
        for (int d = 1; d <= 3; d++) { const uint32_t rb = mapa(sb, hb + (j3 + d) % 3); st_async2(rb + off, x, y, rb + OFF_BAR + B_A); }
      } else if (warp == 7) {
        bar_sync(NB_V, 160);
        if (lane == 0) {
          mbar_expect(bar + B_X, 40960);
          for (int c2 = 0; c2 < 10; c2++) tma2d(sb + OFF_H + c2 * 5120, &tm_x, c2 * 64, (s + 1) * 32, bar + B_X);
        }
        __syncwarp();
      }
      PROF(tid0 >> 7, 2);
      const uint32_t kh = warp & 1;
      const uint32_t wo_l = ((l3 >> 1) * 8 + l7) * 32 + (((l3 & 1) ^ (l7 >> 2)) << 4);
      const uint32_t og = sb + OFF_OG + kh * 3072 + lane * 16;
      const uint32_t bb = bar + B_B + kh * 24;
      uint32_t src = j3;
      if (warp < 4) {
        const uint32_t wo = sb + OFF_WO + (warp >> 1) * 36864 + kh * 6144 + wo_l;
        float v[12];
#pragma unroll
        for (int i = 0; i < 12; i++) v[i] = 0.f;
        uint32_t f[2][12];
#pragma unroll
        for (int i = 0; i < 3; i++) ldsm4t(f[0][4 * i], f[0][4 * i + 1], f[0][4 * i + 2], f[0][4 * i + 3], wo + src * 2048 + i * 12288);
#pragma unroll
        for (int i = 0; i < 3; i++) ldsm4t(f[1][4 * i], f[1][4 * i + 1], f[1][4 * i + 2], f[1][4 * i + 3], wo + src * 2048 + i * 12288 + 512);
#pragma unroll
        for (int u = 0; u < 3; u++) {
          const uint32_t nsrc = src == 0 ? 2 : src - 1;
          mbar_wait_cl(bb + 8 * src, s & 1);
#pragma unroll
          for (int k2 = 0; k2 < 2; k2++) {
            const uint4 o = lds4u(og + src * 1024 + k2 * 512);
#pragma unroll
            for (int k1 = 0; k1 < 2; k1++) {
              uint32_t* ff = f[k1];
#pragma unroll
              for (int i = 0; i < 3; i++) mma16816(v + 4 * i, ff[4 * i], ff[4 * i + 1], ff[4 * i + 2], ff[4 * i + 3], k1 ? o.z : o.x, k1 ? o.w : o.y);
              if (k2 == 0 || u < 2) {
                const uint32_t nx = wo + (k2 == 0 ? src * 2048 + 1024 : nsrc * 2048) + k1 * 512;
#pragma unroll
                for (int i = 0; i < 3; i++) ldsm4t(ff[4 * i], ff[4 * i + 1], ff[4 * i + 2], ff[4 * i + 3], nx + i * 12288);
              }
            }
          }
          src = nsrc;
        }
        mbar_wait_cl(bar + B_B + 8 * rank, s & 1);
        const uint32_t xb = sb + OFF_RA + warp * 768, yb = sb + OFF_RA + (warp ^ 1) * 768;
        sts4f(xb + lane * 16, kh ? v[0] : v[6], kh ? v[1] : v[7], kh ? v[2] : v[8], kh ? v[3] : v[9]);
        sts2f(xb + 512 + lane * 8, kh ? v[4] : v[10], kh ? v[5] : v[11]);
        float4* o = g_acc + (s * ACC_CHUNKS + 2 * rank * 128 + warp * 64 + lane);
        bar_sync(NB_R + (warp >> 1), 64);
        const float4 p = lds4f(yb + lane * 16); const float2 q = lds2f(yb + 512 + lane * 8);
        red4(o, (kh ? v[6] : v[0]) + p.x, (kh ? v[7] : v[1]) + p.y, (kh ? v[8] : v[2]) + p.z, 1.0f);
        red4(o + 32, (kh ? v[9] : v[3]) + p.w, (kh ? v[10] : v[4]) + q.x, (kh ? v[11] : v[5]) + q.y, 1.0f);
      } else if (warp < 6 && rank < 4) {
        const uint32_t wo = sb + OFF_WO + 6 * 12288 + kh * 6144 + wo_l;
        float v[8];
#pragma unroll
        for (int i = 0; i < 8; i++) v[i] = 0.f;
        uint32_t f[16];
#pragma unroll
        for (int u = 0; u < 3; u++) {
#pragma unroll
          for (int kk = 0; kk < 4; kk++) ldsm4t(f[4 * kk], f[4 * kk + 1], f[4 * kk + 2], f[4 * kk + 3], wo + src * 2048 + kk * 512);
          mbar_wait_cl(bb + 8 * src, s & 1);
          const uint4 o0 = lds4u(og + src * 1024), o1 = lds4u(og + src * 1024 + 512);
          mma16816(v, f[0], f[1], f[2], f[3], o0.x, o0.y);
          mma16816(v + 4, f[4], f[5], f[6], f[7], o0.z, o0.w);
          mma16816(v, f[8], f[9], f[10], f[11], o1.x, o1.y);
          mma16816(v + 4, f[12], f[13], f[14], f[15], o1.z, o1.w);
          src = src == 0 ? 2 : src - 1;
        }
#pragma unroll
        for (int i = 0; i < 4; i++) v[i] += v[4 + i];
        mbar_wait_cl(bar + B_B + 8 * rank, s & 1);
        const uint32_t xb = sb + OFF_RA + 3072;
        if (kh) sts4f(xb + lane * 16, v[0], v[1], v[2], 0.f); else sts1f(xb + 512 + lane * 4, v[3]);
        float4* o = g_acc + (s * ACC_CHUNKS + 1536 + rank * 64 + kh * 32 + lane);
        bar_sync(NB_R + 2, 64);
        if (kh) { const float p = lds1f(xb + 512 + lane * 4); red4(o, v[3] + p, 0.f, 0.f, 1.0f); }
        else { const float4 p = lds4f(xb + lane * 16); red4(o, v[0] + p.x, v[1] + p.y, v[2] + p.z, 1.0f); }
      }
      PROF(tid0 >> 7, 3);
      token_qk<true>(a, s, sb, tid0);
    }
    cluster_sync();
  } else {
    asm volatile("setmaxnreg.dec.sync.aligned.u32 88;");
    uint32_t wv[4 * NRF];
    mbar_wait(bar + B_WR, 0);
    {
      const uint32_t l7 = tid0 & 7, l3 = (tid0 >> 3) & 3, w4 = (tid0 >> 5) & 3;
#pragma unroll
      for (int k = 0; k < NRF; k++)
        ldsm4t(wv[4 * k], wv[4 * k + 1], wv[4 * k + 2], wv[4 * k + 3], sb + OFF_Q + k * 2048 + ((l3 >> 1) * 8 + l7) * 128 + (((2 * w4 + (l3 & 1)) ^ l7) << 4));
    }
    bar_arrive(NB_TS, 384);
    mbar_wait(bar + B_W, 0);
    const float sc = 0.07216878364870322f * 1.4426950408889634f;

    for (int s = 0; s < NSEG; s++) {
      const bool last = s == NSEG - 1;
      mbar_wait(bar + B_X, s & 1);
      uint32_t va[10];
      {
        float v[20];
        uint64_t db = mkdesc(sb + OFF_H, 16, 1024, 1), da = mkdesc(sb + OFF_WV, 1024, 1024, 1);
        OPAQUE64(db); OPAQUE64(da);
        bar_sync(NB_M, 384);
        PROF(2, 0);
        WG_FENCE();
        wg_ss40<0, 1>(v, da, db);
#pragma unroll
        for (int k = 1; k < NSS; k++) wg_ss40<1, 1>(v, da + (uint64_t)(k * 128), db + HOFF(k));
#pragma unroll
        for (int k = NSS; k < 40; k++) wg_rs40<1>(v, wv[4 * (k - NSS)], wv[4 * (k - NSS) + 1], wv[4 * (k - NSS) + 2], wv[4 * (k - NSS) + 3], db + HOFF(k));
        WG_COMMIT();
        WG_WAIT(0);
#pragma unroll
        for (int i = 0; i < 10; i++) va[i] = pack2(v[2 * i], v[2 * i + 1]);
      }
      PROF(2, 1);
      if (!last) {
        bar_arrive(NB_V, 160);
        const uint32_t tid = opq(tid0), lane = tid & 31, w4 = (tid >> 5) & 3;
        const uint32_t ra = sb + OFF_RA + lane * 8;
        const uint32_t off = OFF_OG + rank * 1024 + (w4 >> 1) * 512 + lane * 16 + (w4 & 1) * 8;
        mbar_wait_cl(bar + B_A, s & 1);
        PROF(2, 2);
        float p[10];
#pragma unroll
        for (int i = 0; i < 5; i++) {
          const float2 x = lds2f(ra + i * 256), y = lds2f(ra + i * 256 + 1280), z = lds2f(ra + i * 256 + 2560);
          p[2 * i] = (x.x + y.x) + z.x; p[2 * i + 1] = (x.y + y.y) + z.y;
        }
        float mx = p[0];
#pragma unroll
        for (int i = 1; i < 10; i++) mx = fmaxf(mx, p[i]);
        mx = fmaxf(mx, __shfl_xor_sync(~0u, mx, 1)); mx = fmaxf(mx, __shfl_xor_sync(~0u, mx, 2));
        float sum = 0.f;
#pragma unroll
        for (int i = 0; i < 10; i++) { p[i] = exp2f((p[i] - mx) * sc); sum += p[i]; }
        sum += __shfl_xor_sync(~0u, sum, 1); sum += __shfl_xor_sync(~0u, sum, 2);
        const float inv = 1.0f / sum;
        uint32_t pa[5];
#pragma unroll
        for (int i = 0; i < 5; i++) pa[i] = pack2(p[2 * i] * inv, p[2 * i + 1] * inv);
        float o0[4] = {0.f, 0.f, 0.f, 0.f}, o1[4] = {0.f, 0.f, 0.f, 0.f}, o2[4] = {0.f, 0.f, 0.f, 0.f}, o3[4] = {0.f, 0.f, 0.f, 0.f};
        mma16816(o0, pa[0], 0u, pa[1], 0u, va[0], va[2]);
        mma16816(o1, pa[0], 0u, pa[1], 0u, va[1], va[3]);
        mma16816(o2, pa[2], 0u, pa[3], 0u, va[4], va[6]);
        mma16816(o3, pa[2], 0u, pa[3], 0u, va[5], va[7]);
        mma16816(o0, pa[4], 0u, 0u, 0u, va[8], 0u);
        mma16816(o1, pa[4], 0u, 0u, 0u, va[9], 0u);
        const uint32_t x = pack2(o0[0] + o2[0], o0[1] + o2[1]), y = pack2(o1[0] + o3[0], o1[1] + o3[1]);
#pragma unroll
        for (int d = 0; d < CL; d++) {
          int r = rank + d; if (r >= CL) r -= CL;
          const uint32_t rb = mapa(sb, r);
          st_async2(rb + off, x, y, rb + OFF_BAR + B_B + 8 * rank);
        }
        if (tid == 256) mbar_expect(bar + B_A, 3 * 1280);
        PROF(2, 3);
      }
      bar_sync(NB_K2, 384);
      float p[10];
      {
        float v[20];
        uint64_t da = mkdesc(sb + OFF_Q, 16, 512, 1), db = mkdesc(sb + OFF_K, 16, 1024, 1);
        OPAQUE64(db); OPAQUE64(da);
        WG_FENCE();
        wg_ss40<0, 0>(v, da, db);
        wg_ss40<1, 0>(v, da + 2, db + 2);
        wg_ss40<1, 0>(v, da + 4, db + 4);
        wg_ss40<1, 0>(v, da + 6, db + 6);
        WG_COMMIT();
        WG_WAIT(0);
#pragma unroll
        for (int i = 0; i < 5; i++) { p[2 * i] = v[4 * i]; p[2 * i + 1] = v[4 * i + 1]; }
      }
      const uint32_t tid = opq(tid0), wt = tid - 256, lane = tid & 31, w4 = wt >> 5;
      const uint32_t rt = (last ? OFF_WO : OFF_H + 4096) + wt * 8;
      if (!last) {
#pragma unroll
        for (int i = 0; i < CL; i++) mbar_wait_cl(bar + B_B + 8 * i, s & 1);
        if (wt < CL) mbar_expect(bar + B_B + 8 * wt, 1024);
      }
      PROF(2, 4);
#pragma unroll
      for (int d = 1; d <= 2; d++) {
        const uint32_t rb = mapa(sb, hb + (j3 + d) % 3);
#pragma unroll
        for (int i = 0; i < 5; i++)
          st_async2(rb + rt + ((2 - d) * 5 + i) * 5120, __float_as_uint(p[2 * i]), __float_as_uint(p[2 * i + 1]), rb + OFF_BAR + B_T);
      }
      mbar_wait_cl(bar + B_T, s & 1);
      PROF(2, 5);
#pragma unroll
      for (int i = 0; i < 5; i++) {
        const float2 x = lds2f(sb + rt + i * 5120), y = lds2f(sb + rt + (5 + i) * 5120);
        p[2 * i] += x.x + y.x; p[2 * i + 1] += x.y + y.y;
      }
      if (wt == 0) mbar_expect(bar + B_T, 2 * 5120);
      MemLoad ml; float4 mx0, mx1;
      const int sl = last ? 0 : s;
      const float4* accx = g_acc + (sl * ACC_CHUNKS + 1536 + w4 * 64 + lane);
      memload_issue(ml, sl, tid);
      mx0 = ld_relaxed4(accx); mx1 = ld_relaxed4(accx + 32);
      {
        const int tq = 8 * (lane >> 3) + 2 * w4 + ((lane >> 2) & 1) - 2 * (lane & 3);
        float mx = fmaxf(p[8], p[9]);
#pragma unroll
        for (int i = 0; i < 8; i++) { if (8 * (i >> 1) + (i & 1) > tq) p[i] = -INFINITY; mx = fmaxf(mx, p[i]); }
        mx = fmaxf(mx, __shfl_xor_sync(~0u, mx, 1)); mx = fmaxf(mx, __shfl_xor_sync(~0u, mx, 2));
        if (!last) bar_arrive(NB_TS, 384);
        float sum = 0.f;
#pragma unroll
        for (int i = 0; i < 10; i++) { p[i] = exp2f((p[i] - mx) * sc); sum += p[i]; }
        sum += __shfl_xor_sync(~0u, sum, 1); sum += __shfl_xor_sync(~0u, sum, 2);
        const float inv = 1.0f / sum;
#pragma unroll
        for (int i = 0; i < 5; i++) sts1u(sb + OFF_P + w4 * 768 + i * 128 + lane * 4, pack2(p[2 * i] * inv, p[2 * i + 1] * inv));
      }
      fence_async();
      bar_sync(NB_P, 128);
      {
        float o[16];
        uint64_t db = mkdesc(sb + OFF_P, 128, 768, 0);
        OPAQUE64(db);
        WG_FENCE();
        wg_rs32<0>(o, va[0], va[1], va[2], va[3], db);
        wg_rs32<1>(o, va[4], va[5], va[6], va[7], db + 16);
        wg_rs32<1>(o, va[8], va[9], 0u, 0u, db + 32);
        WG_COMMIT();
        uint4* dst = reinterpret_cast<uint4*>(g_oT) + ((s * HD + blockIdx.x * 64 + w4 * 16) * 4 + lane);
        WG_WAIT(0);
        dst[0] = make_uint4(pack2(o[0], o[1]), pack2(o[4], o[5]), pack2(o[8], o[9]), pack2(o[12], o[13]));
        dst[32] = make_uint4(pack2(o[2], o[3]), pack2(o[6], o[7]), pack2(o[10], o[11]), pack2(o[14], o[15]));
      }
      PROF(2, 6);
      if (!last) {
        memload_finish(ml, s, opq(tid0), sb);
        int n = 0;
        while (!__all_sync(~0u, mx0.w == (float)NCL && mx1.w == (float)NCL)) {
          if (++n > SPIN_LIMIT) __trap();
          mx0 = ld_relaxed4(accx); mx1 = ld_relaxed4(accx + 32);
        }
        stsm2t(memrow_addr(sb, 576 + w4 * 16 + ((lane >> 3) & 1) * 8, lane & 7), pack2(mx0.x, mx0.y), pack2(mx0.z, mx1.x));
        fence_async();
      }
      PROF(2, 7);
    }
    cluster_sync();
  }
}

namespace g1 { constexpr int STAGES = 4, STAGE = 49152, SMEM = STAGES * STAGE + 1024; }
__global__ void __launch_bounds__(384, 1)
g1_kernel(const __grid_constant__ CUtensorMap tm_a, const __grid_constant__ CUtensorMap tm_g, const __grid_constant__ CUtensorMap tm_u) {
  using namespace g1;
  extern __shared__ __align__(1024) unsigned char smem[];
  const uint32_t sb = smem_u32(smem), bar = sb + STAGES * STAGE;
  const int tid = threadIdx.x, lane = tid & 31, wg = tid >> 7;
  const int m0 = (blockIdx.x / 12) * 128, n0 = (blockIdx.x % 12) * 128;
  if (tid == 0) { for (int i = 0; i < STAGES; i++) { mbar_init(bar + 8 * i, 1); mbar_init(bar + 64 + 8 * i, 2); } asm volatile("fence.mbarrier_init.release.cluster;" ::: "memory"); }
  __syncthreads();
  if (wg == 2) {
    asm volatile("setmaxnreg.dec.sync.aligned.u32 40;");
    if (tid == 256) {
      for (int kb = 0; kb < 10; kb++) {
        const int st = kb % STAGES; const uint32_t base = sb + st * STAGE;
        mbar_wait(bar + 64 + 8 * st, ((kb / STAGES) & 1) ^ 1);
        mbar_expect(bar + 8 * st, STAGE);
        tma2d(base, &tm_a, kb * 64, m0, bar + 8 * st);
        tma2d(base + 16384, &tm_g, n0, kb * 64, bar + 8 * st);
        tma2d(base + 24576, &tm_g, n0 + 64, kb * 64, bar + 8 * st);
        tma2d(base + 32768, &tm_u, n0, kb * 64, bar + 8 * st);
        tma2d(base + 40960, &tm_u, n0 + 64, kb * 64, bar + 8 * st);
      }
    }
  } else {
    asm volatile("setmaxnreg.inc.sync.aligned.u32 232;");
    float dg[64], du[64];
#pragma unroll
    for (int i = 0; i < 64; i++) { dg[i] = 0.f; du[i] = 0.f; }
    for (int kb = 0; kb < 10; kb++) {
      const int st = kb % STAGES; const uint32_t base = sb + st * STAGE;
      mbar_wait(bar + 8 * st, (kb / STAGES) & 1);
      uint64_t da = mkdesc(base + wg * 8192, 16, 1024, 1), db = mkdesc(base + 16384, 8192, 1024, 1);
      WG_FENCE();
#pragma unroll
      for (int k = 0; k < 4; k++) { wg_ss128<0>(dg, da + 2 * k, db + 128 * k); wg_ss128<0>(du, da + 2 * k, db + 1024 + 128 * k); }
      WG_COMMIT();
      WG_WAIT(0);
      if ((tid & 127) == 0) mbar_arrive(bar + 64 + 8 * st);
    }
    const int row = m0 + wg * 64 + ((tid >> 5) & 3) * 16 + (lane >> 2);
    uint32_t* o = reinterpret_cast<uint32_t*>(g_h + (size_t)row * FF + n0 + (lane & 3) * 2);
#pragma unroll
    for (int j = 0; j < 16; j++) {
      o[j * 4] = pack2(bfr(dg[4 * j]) * bfr(du[4 * j]), bfr(dg[4 * j + 1]) * bfr(du[4 * j + 1]));
      o[j * 4 + 4 * FF] = pack2(bfr(dg[4 * j + 2]) * bfr(du[4 * j + 2]), bfr(dg[4 * j + 3]) * bfr(du[4 * j + 3]));
    }
  }
}

namespace g2 { constexpr int STAGES = 6, STAGE = 32768, SMEM = STAGES * STAGE + 1024, KB_H = FF / 64, KB = KB_H + HD / 64; }
__global__ void __launch_bounds__(384, 1)
g2_kernel(const __grid_constant__ CUtensorMap tm_h, const __grid_constant__ CUtensorMap tm_o, const __grid_constant__ CUtensorMap tm_wd,
          const __grid_constant__ CUtensorMap tm_wo, const bf16* __restrict__ x, bf16* __restrict__ out) {
  using namespace g2;
  extern __shared__ __align__(1024) unsigned char smem[];
  const uint32_t sb = smem_u32(smem), bar = sb + STAGES * STAGE;
  const int tid = threadIdx.x, lane = tid & 31, wg = tid >> 7;
  const int m0 = (blockIdx.x / 5) * 128, n0 = (blockIdx.x % 5) * 128;
  if (tid == 0) { for (int i = 0; i < STAGES; i++) { mbar_init(bar + 8 * i, 1); mbar_init(bar + 64 + 8 * i, 2); } asm volatile("fence.mbarrier_init.release.cluster;" ::: "memory"); }
  __syncthreads();
  if (wg == 2) {
    asm volatile("setmaxnreg.dec.sync.aligned.u32 40;");
    if (tid == 256) {
      for (int kb = 0; kb < KB; kb++) {
        const int st = kb % STAGES; const uint32_t base = sb + st * STAGE;
        mbar_wait(bar + 64 + 8 * st, ((kb / STAGES) & 1) ^ 1);
        mbar_expect(bar + 8 * st, STAGE);
        if (kb < KB_H) {
          tma2d(base, &tm_h, kb * 64, m0, bar + 8 * st);
          tma2d(base + 16384, &tm_wd, n0, kb * 64, bar + 8 * st);
          tma2d(base + 24576, &tm_wd, n0 + 64, kb * 64, bar + 8 * st);
        } else {
          const int k0 = (kb - KB_H) * 64;
          tma3d(base, &tm_o, 0, k0, m0 / 32, bar + 8 * st);
          tma2d(base + 16384, &tm_wo, n0, k0, bar + 8 * st);
          tma2d(base + 24576, &tm_wo, n0 + 64, k0, bar + 8 * st);
        }
      }
    }
  } else {
    asm volatile("setmaxnreg.inc.sync.aligned.u32 232;");
    float d[64];
#pragma unroll
    for (int i = 0; i < 64; i++) d[i] = 0.f;
    for (int kb = 0; kb < KB; kb++) {
      const int st = kb % STAGES; const uint32_t base = sb + st * STAGE;
      mbar_wait(bar + 8 * st, (kb / STAGES) & 1);
      const uint64_t db = mkdesc(base + 16384, 8192, 1024, 1);
      WG_FENCE();
      if (kb < KB_H) {
        const uint64_t da = mkdesc(base + wg * 8192, 16, 1024, 1);
#pragma unroll
        for (int k = 0; k < 4; k++) wg_ss128<0>(d, da + 2 * k, db + 128 * k);
      } else {
        const uint64_t da = mkdesc(base + wg * 8192, 4096, 512, 2);
#pragma unroll
        for (int k = 0; k < 4; k++) wg_ss128<1>(d, da + 64 * k, db + 128 * k);
      }
      WG_COMMIT();
      WG_WAIT(1);
      if (kb > 0 && (tid & 127) == 0) mbar_arrive(bar + 64 + 8 * ((kb - 1) % STAGES));
    }
    WG_WAIT(0);
    const int row = m0 + wg * 64 + ((tid >> 5) & 3) * 16 + (lane >> 2);
    const size_t off = (size_t)row * DM + n0 + (lane & 3) * 2;
    const uint32_t* xi = reinterpret_cast<const uint32_t*>(x + off);
    uint32_t* o = reinterpret_cast<uint32_t*>(out + off);
#pragma unroll
    for (int j = 0; j < 16; j++) {
      const uint32_t x0 = __ldg(xi + j * 4), x1 = __ldg(xi + j * 4 + 4 * DM);
      o[j * 4] = pack2(d[4 * j] + __uint_as_float(x0 << 16), d[4 * j + 1] + __uint_as_float(x0 & 0xffff0000u));
      o[j * 4 + 4 * DM] = pack2(d[4 * j + 2] + __uint_as_float(x1 << 16), d[4 * j + 3] + __uint_as_float(x1 & 0xffff0000u));
    }
  }
}

typedef CUresult (*EncodeFn)(CUtensorMap*, CUtensorMapDataType, cuuint32_t, void*, const cuuint64_t*, const cuuint64_t*, const cuuint32_t*,
                             const cuuint32_t*, CUtensorMapInterleave, CUtensorMapSwizzle, CUtensorMapL2promotion, CUtensorMapFloatOOBfill);
static void make_map(EncodeFn enc, CUtensorMap* m, const void* p, int rank, const cuuint64_t* dims, const cuuint64_t* strides,
                     const cuuint32_t* box, CUtensorMapSwizzle swz) {
  cuuint32_t es[3] = {1, 1, 1};
  enc(m, CU_TENSOR_MAP_DATA_TYPE_BFLOAT16, rank, const_cast<void*>(p), dims, strides, box, es, CU_TENSOR_MAP_INTERLEAVE_NONE, swz,
      CU_TENSOR_MAP_L2_PROMOTION_L2_128B, CU_TENSOR_MAP_FLOAT_OOB_FILL_NONE);
}
static void map2d(EncodeFn enc, CUtensorMap* m, const void* p, int cols, int rows, int bc, int br, CUtensorMapSwizzle swz) {
  cuuint64_t dims[2] = {(cuuint64_t)cols, (cuuint64_t)rows}, strides[1] = {(cuuint64_t)cols * 2};
  cuuint32_t box[2] = {(cuuint32_t)bc, (cuuint32_t)br};
  make_map(enc, m, p, 2, dims, strides, box, swz);
}

extern "C" void kernel_launch(void* const* d_in, const int* in_sizes, int n_in, void* d_out, int out_size) {
  const bf16* x = (const bf16*)d_in[0];
  const bf16* mem0 = (const bf16*)d_in[1];
  const bf16* Wq = (const bf16*)d_in[2];
  const bf16* Wk = (const bf16*)d_in[3];
  const bf16* Wv = (const bf16*)d_in[4];
  const bf16* Wo = (const bf16*)d_in[5];
  const bf16* Wg = (const bf16*)d_in[8];
  const bf16* Wu = (const bf16*)d_in[9];
  const bf16* Wd = (const bf16*)d_in[10];
  bf16* out = (bf16*)d_out;

  void* fn = nullptr; cudaDriverEntryPointQueryResult qr;
  cudaGetDriverEntryPoint("cuTensorMapEncodeTiled", &fn, cudaEnableDefault, &qr);
  EncodeFn enc = (EncodeFn)fn;
  void *p_xn, *p_oT, *p_h;
  cudaGetSymbolAddress(&p_xn, g_xn); cudaGetSymbolAddress(&p_oT, g_oT); cudaGetSymbolAddress(&p_h, g_h);

  CUtensorMap t_x32, t_wv, t_wo16, t_x128, t_wg, t_wu, t_h, t_o, t_wd, t_wo64;
  map2d(enc, &t_x32, p_xn, DM, SEQ, 64, 32, CU_TENSOR_MAP_SWIZZLE_128B);
  map2d(enc, &t_wv, Wv, HD, DM, 64, 80, CU_TENSOR_MAP_SWIZZLE_128B);
  map2d(enc, &t_wo16, Wo, DM, HD, 16, 192, CU_TENSOR_MAP_SWIZZLE_32B);
  map2d(enc, &t_x128, p_xn, DM, SEQ, 64, 128, CU_TENSOR_MAP_SWIZZLE_128B);
  map2d(enc, &t_wg, Wg, FF, DM, 64, 64, CU_TENSOR_MAP_SWIZZLE_128B);
  map2d(enc, &t_wu, Wu, FF, DM, 64, 64, CU_TENSOR_MAP_SWIZZLE_128B);
  map2d(enc, &t_h, p_h, FF, SEQ, 64, 128, CU_TENSOR_MAP_SWIZZLE_128B);
  map2d(enc, &t_wd, Wd, DM, FF, 64, 64, CU_TENSOR_MAP_SWIZZLE_128B);
  map2d(enc, &t_wo64, Wo, DM, HD, 64, 64, CU_TENSOR_MAP_SWIZZLE_128B);
  {
    cuuint64_t dims[3] = {32, (cuuint64_t)HD, (cuuint64_t)NSEG}, strides[2] = {64, (cuuint64_t)HD * 64};
    cuuint32_t box[3] = {32, 64, 4};
    make_map(enc, &t_o, p_oT, 3, dims, strides, box, CU_TENSOR_MAP_SWIZZLE_64B);
  }
  cudaFuncSetAttribute(chain_kernel, cudaFuncAttributeMaxDynamicSharedMemorySize, ck::SMEM);
  cudaFuncSetAttribute(g1_kernel, cudaFuncAttributeMaxDynamicSharedMemorySize, g1::SMEM);
  cudaFuncSetAttribute(g2_kernel, cudaFuncAttributeMaxDynamicSharedMemorySize, g2::SMEM);

  cudaStream_t st = cudaStreamPerThread;
  ln_kernel<<<256, 256, 0, st>>>(x);
  g1_kernel<<<192, 384, g1::SMEM, st>>>(t_x128, t_wg, t_wu);
  {
    cudaLaunchConfig_t cfg = {};
    cfg.gridDim = dim3(ck::CL * ck::NCL); cfg.blockDim = dim3(384); cfg.dynamicSmemBytes = ck::SMEM; cfg.stream = st;
    cudaLaunchAttribute at[1];
    at[0].id = cudaLaunchAttributeClusterDimension; at[0].val.clusterDim.x = ck::CL; at[0].val.clusterDim.y = 1; at[0].val.clusterDim.z = 1;
    cfg.attrs = at; cfg.numAttrs = 1;
    cudaLaunchKernelEx(&cfg, chain_kernel, t_x32, t_wv, t_wo16, Wq, Wk, mem0);
  }
  g2_kernel<<<80, 384, g2::SMEM, st>>>(t_h, t_o, t_wd, t_wo64, x, out);
}
```

```cpp
#include <cuda_runtime.h>
#include <cuda_bf16.h>
#include <cuda.h>
#include <stdint.h>

typedef __nv_bfloat16 bf16;

constexpr int SEQ = 2048, DM = 640, HD = 6144, FF = 1536, NSEG = 64;
constexpr int ACC_CHUNKS = 1792;

__device__ bf16 g_xn[SEQ * DM];
__device__ bf16 g_oT[NSEG * HD * 32];
__device__ bf16 g_h[SEQ * FF];
__device__ float4 g_acc[NSEG * ACC_CHUNKS];
__device__ float4 g_part[20 * 4096];
__device__ unsigned g_flag[64];
#define CK_EXTRA 0
#define HPROF(i, k) do {} while (0)
#define PROF(who, slot) do {} while (0)

__device__ __forceinline__ uint32_t smem_u32(const void* p) { return (uint32_t)__cvta_generic_to_shared(p); }
__device__ __forceinline__ uint32_t mapa(uint32_t a, uint32_t r) { uint32_t o; asm("mapa.shared::cluster.u32 %0, %1, %2;" : "=r"(o) : "r"(a), "r"(r)); return o; }
__device__ __forceinline__ void mbar_init(uint32_t b, int c) { asm volatile("mbarrier.init.shared::cta.b64 [%0], %1;" :: "r"(b), "r"(c) : "memory"); }
__device__ __forceinline__ void mbar_expect(uint32_t b, uint32_t bytes) { asm volatile("mbarrier.arrive.expect_tx.shared::cta.b64 _, [%0], %1;" :: "r"(b), "r"(bytes) : "memory"); }
__device__ __forceinline__ void mbar_arrive(uint32_t b) { asm volatile("mbarrier.arrive.shared::cta.b64 _, [%0];" :: "r"(b) : "memory"); }
constexpr int SPIN_LIMIT = 1 << 20;
__device__ __forceinline__ void mbar_wait(uint32_t b, uint32_t ph) {
  asm volatile("{\n.reg .pred p;\n.reg .u32 n;\nmov.u32 n, 0;\n"
               "W: mbarrier.try_wait.parity.shared::cta.b64 p, [%0], %1;\n@p bra D;\n"
               "add.u32 n, n, 1;\nsetp.lt.u32 p, n, 0x40000;\n@p bra W;\ntrap;\nD:\n}" :: "r"(b), "r"(ph) : "memory");
}
__device__ __forceinline__ void mbar_wait_long(uint32_t b, uint32_t ph) {
  asm volatile("{\n.reg .pred p;\n.reg .u32 n;\nmov.u32 n, 0;\n"
               "W: mbarrier.try_wait.parity.shared::cta.b64 p, [%0], %1;\n@p bra D;\n"
               "add.u32 n, n, 1;\nsetp.lt.u32 p, n, 0x400000;\n@p bra W;\ntrap;\nD:\n}" :: "r"(b), "r"(ph) : "memory");
}
__device__ __forceinline__ void bar_sync(int id, int n) { asm volatile("bar.sync %0, %1;" :: "r"(id), "r"(n) : "memory"); }
__device__ __forceinline__ void bar_arrive(int id, int n) { asm volatile("bar.arrive %0, %1;" :: "r"(id), "r"(n) : "memory"); }
__device__ __forceinline__ void fence_async() { asm volatile("fence.proxy.async.shared::cta;" ::: "memory"); }
__device__ __forceinline__ void cluster_sync() { asm volatile("barrier.cluster.arrive.release.aligned;\nbarrier.cluster.wait.acquire.aligned;" ::: "memory"); }
__device__ __forceinline__ void tma2d(uint32_t dst, const CUtensorMap* m, int c0, int c1, uint32_t bar) {
  asm volatile("cp.async.bulk.tensor.2d.shared::cluster.global.mbarrier::complete_tx::bytes [%0], [%1, {%3, %4}], [%2];"
               :: "r"(dst), "l"(m), "r"(bar), "r"(c0), "r"(c1) : "memory");
}
__device__ __forceinline__ void tma2d_mc(uint32_t dst, const CUtensorMap* m, int c0, int c1, uint32_t bar, uint16_t mask) {
  asm volatile("cp.async.bulk.tensor.2d.shared::cluster.global.mbarrier::complete_tx::bytes.multicast::cluster [%0], [%1, {%3, %4}], [%2], %5;"
               :: "r"(dst), "l"(m), "r"(bar), "r"(c0), "r"(c1), "h"(mask) : "memory");
}
__device__ __forceinline__ void tma3d(uint32_t dst, const CUtensorMap* m, int c0, int c1, int c2, uint32_t bar) {
  asm volatile("cp.async.bulk.tensor.3d.shared::cluster.global.mbarrier::complete_tx::bytes [%0], [%1, {%3, %4, %5}], [%2];"
               :: "r"(dst), "l"(m), "r"(bar), "r"(c0), "r"(c1), "r"(c2) : "memory");
}
__device__ __forceinline__ void st_async1(uint32_t a, uint32_t x, uint32_t mb) {
  asm volatile("st.async.weak.shared::cluster.mbarrier::complete_tx::bytes.b32 [%0], %1, [%2];" :: "r"(a), "r"(x), "r"(mb) : "memory");
}
__device__ __forceinline__ void st_async2(uint32_t a, uint32_t x, uint32_t y, uint32_t mb) {
  asm volatile("st.async.weak.shared::cluster.mbarrier::complete_tx::bytes.v2.b32 [%0], {%1,%2}, [%3];" :: "r"(a), "r"(x), "r"(y), "r"(mb) : "memory");
}
__device__ __forceinline__ void st_async4(uint32_t a, uint32_t x, uint32_t y, uint32_t z, uint32_t w, uint32_t mb) {
  asm volatile("st.async.weak.shared::cluster.mbarrier::complete_tx::bytes.v4.b32 [%0], {%1,%2,%3,%4}, [%5];" :: "r"(a), "r"(x), "r"(y), "r"(z), "r"(w), "r"(mb) : "memory");
}
__device__ __forceinline__ void ldsm4(uint32_t& r0, uint32_t& r1, uint32_t& r2, uint32_t& r3, uint32_t a) {
  asm volatile("ldmatrix.sync.aligned.m8n8.x4.shared.b16 {%0,%1,%2,%3}, [%4];" : "=r"(r0), "=r"(r1), "=r"(r2), "=r"(r3) : "r"(a) : "memory");
}
__device__ __forceinline__ void ldsm4t(uint32_t& r0, uint32_t& r1, uint32_t& r2, uint32_t& r3, uint32_t a) {
  asm volatile("ldmatrix.sync.aligned.m8n8.x4.trans.shared.b16 {%0,%1,%2,%3}, [%4];" : "=r"(r0), "=r"(r1), "=r"(r2), "=r"(r3) : "r"(a) : "memory");
}
__device__ __forceinline__ void stsm4t(uint32_t a, uint32_t r0, uint32_t r1, uint32_t r2, uint32_t r3) {
  asm volatile("stmatrix.sync.aligned.m8n8.x4.trans.shared.b16 [%0], {%1,%2,%3,%4};" :: "r"(a), "r"(r0), "r"(r1), "r"(r2), "r"(r3) : "memory");
}
__device__ __forceinline__ void stsm1t(uint32_t a, uint32_t r0) {
  asm volatile("stmatrix.sync.aligned.m8n8.x1.trans.shared.b16 [%0], {%1};" :: "r"(a), "r"(r0) : "memory");
}
__device__ __forceinline__ void stsm2t(uint32_t a, uint32_t r0, uint32_t r1) {
  asm volatile("stmatrix.sync.aligned.m8n8.x2.trans.shared.b16 [%0], {%1,%2};" :: "r"(a), "r"(r0), "r"(r1) : "memory");
}
__device__ __forceinline__ void mma16816(float* d, uint32_t a0, uint32_t a1, uint32_t a2, uint32_t a3, uint32_t b0, uint32_t b1) {
  asm volatile("mma.sync.aligned.m16n8k16.row.col.f32.bf16.bf16.f32 {%0,%1,%2,%3}, {%4,%5,%6,%7}, {%8,%9}, {%0,%1,%2,%3};"
               : "+f"(d[0]), "+f"(d[1]), "+f"(d[2]), "+f"(d[3]) : "r"(a0), "r"(a1), "r"(a2), "r"(a3), "r"(b0), "r"(b1));
}
__device__ __forceinline__ float ex2(float x) { float r; asm("ex2.approx.ftz.f32 %0, %1;" : "=f"(r) : "f"(x)); return r; }
__device__ __forceinline__ float rcp(float x) { float r; asm("rcp.approx.ftz.f32 %0, %1;" : "=f"(r) : "f"(x)); return r; }
__device__ __forceinline__ uint32_t pack2(float lo, float hi) { uint32_t r; asm("cvt.rn.bf16x2.f32 %0, %1, %2;" : "=r"(r) : "f"(hi), "f"(lo)); return r; }
__device__ __forceinline__ float2 lds2f(uint32_t a) { float2 v; asm volatile("ld.shared.v2.f32 {%0,%1}, [%2];" : "=f"(v.x), "=f"(v.y) : "r"(a) : "memory"); return v; }
__device__ __forceinline__ float4 lds4f(uint32_t a) { float4 v; asm volatile("ld.shared.v4.f32 {%0,%1,%2,%3}, [%4];" : "=f"(v.x), "=f"(v.y), "=f"(v.z), "=f"(v.w) : "r"(a) : "memory"); return v; }
__device__ __forceinline__ uint4 lds4u(uint32_t a) { uint4 v; asm volatile("ld.shared.v4.u32 {%0,%1,%2,%3}, [%4];" : "=r"(v.x), "=r"(v.y), "=r"(v.z), "=r"(v.w) : "r"(a) : "memory"); return v; }
__device__ __forceinline__ float lds1f(uint32_t a) { float v; asm volatile("ld.shared.f32 %0, [%1];" : "=f"(v) : "r"(a) : "memory"); return v; }
__device__ __forceinline__ void sts4f(uint32_t a, float x, float y, float z, float w) { asm volatile("st.shared.v4.f32 [%0], {%1,%2,%3,%4};" :: "r"(a), "f"(x), "f"(y), "f"(z), "f"(w) : "memory"); }
__device__ __forceinline__ void sts2f(uint32_t a, float x, float y) { asm volatile("st.shared.v2.f32 [%0], {%1,%2};" :: "r"(a), "f"(x), "f"(y) : "memory"); }
__device__ __forceinline__ void sts1f(uint32_t a, float x) { asm volatile("st.shared.f32 [%0], %1;" :: "r"(a), "f"(x) : "memory"); }
__device__ __forceinline__ void sts1u(uint32_t a, uint32_t x) { asm volatile("st.shared.u32 [%0], %1;" :: "r"(a), "r"(x) : "memory"); }
__device__ __forceinline__ void sts4u(uint32_t a, uint4 v) { asm volatile("st.shared.v4.u32 [%0], {%1,%2,%3,%4};" :: "r"(a), "r"(v.x), "r"(v.y), "r"(v.z), "r"(v.w) : "memory"); }
__device__ __forceinline__ float4 ld_relaxed4(const float4* p) {
  float4 r; asm volatile("ld.relaxed.gpu.global.v4.f32 {%0,%1,%2,%3}, [%4];" : "=f"(r.x), "=f"(r.y), "=f"(r.z), "=f"(r.w) : "l"(p) : "memory"); return r;
}
__device__ __forceinline__ void red4(float4* p, float a, float b, float c, float d) {
  asm volatile("red.relaxed.gpu.global.add.v4.f32 [%0], {%1,%2,%3,%4};" :: "l"(p), "f"(a), "f"(b), "f"(c), "f"(d) : "memory");
}
__device__ __forceinline__ uint64_t mkdesc(uint32_t addr, uint32_t lbo, uint32_t sbo, uint32_t swz) {
  return (uint64_t)((addr & 0x3FFFF) >> 4) | ((uint64_t)(lbo >> 4) << 16) | ((uint64_t)(sbo >> 4) << 32) | ((uint64_t)swz << 62);
}
#define WG_FENCE() asm volatile("wgmma.fence.sync.aligned;" ::: "memory")
#define WG_COMMIT() asm volatile("wgmma.commit_group.sync.aligned;" ::: "memory")
#define WG_WAIT(n) asm volatile("wgmma.wait_group.sync.aligned %0;" :: "n"(n) : "memory")
#define OPAQUE64(x) asm volatile("" : "+l"(x))

#define F4(d, i) "+f"(d[i]), "+f"(d[i + 1]), "+f"(d[i + 2]), "+f"(d[i + 3])
#define F16(d, i) F4(d, i), F4(d, i + 4), F4(d, i + 8), F4(d, i + 12)
template <int ACC>
__device__ __forceinline__ void wg_rs32(float* d, uint32_t a0, uint32_t a1, uint32_t a2, uint32_t a3, uint64_t b) {
  asm volatile("wgmma.mma_async.sync.aligned.m64n32k16.f32.bf16.bf16 {%0,%1,%2,%3,%4,%5,%6,%7,%8,%9,%10,%11,%12,%13,%14,%15}, {%16,%17,%18,%19}, %20, %21, 1, 1, 0;"
               : F16(d, 0) : "r"(a0), "r"(a1), "r"(a2), "r"(a3), "l"(b), "n"(ACC));
}
template <int ACC>
__device__ __forceinline__ void wg_rs32x(float* d, uint32_t a0, uint32_t a1, uint32_t a2, uint32_t a3, uint32_t blo) {
  asm volatile("{\n.reg .b64 b;\nmov.b64 b, {%20, 0x40000040};\n"
               "wgmma.mma_async.sync.aligned.m64n32k16.f32.bf16.bf16 {%0,%1,%2,%3,%4,%5,%6,%7,%8,%9,%10,%11,%12,%13,%14,%15}, {%16,%17,%18,%19}, b, %21, 1, 1, 0;\n}"
               : F16(d, 0) : "r"(a0), "r"(a1), "r"(a2), "r"(a3), "r"(blo), "n"(ACC));
}
template <int ACC>
__device__ __forceinline__ void wg_rs40(float* d, uint32_t a0, uint32_t a1, uint32_t a2, uint32_t a3, uint64_t b) {
  asm volatile("wgmma.mma_async.sync.aligned.m64n40k16.f32.bf16.bf16 {%0,%1,%2,%3,%4,%5,%6,%7,%8,%9,%10,%11,%12,%13,%14,%15,%16,%17,%18,%19}, {%20,%21,%22,%23}, %24, %25, 1, 1, 0;"
               : F16(d, 0), F4(d, 16) : "r"(a0), "r"(a1), "r"(a2), "r"(a3), "l"(b), "n"(ACC));
}
template <int ACC, int TA>
__device__ __forceinline__ void wg_ss40(float* d, uint64_t a, uint64_t b) {
  asm volatile("wgmma.mma_async.sync.aligned.m64n40k16.f32.bf16.bf16 {%0,%1,%2,%3,%4,%5,%6,%7,%8,%9,%10,%11,%12,%13,%14,%15,%16,%17,%18,%19}, %20, %21, %22, 1, 1, %23, 0;"
               : F16(d, 0), F4(d, 16) : "l"(a), "l"(b), "n"(ACC), "n"(TA));
}
template <int TA>
__device__ __forceinline__ void wg_ss128(float* d, uint64_t a, uint64_t b) {
  asm volatile("wgmma.mma_async.sync.aligned.m64n128k16.f32.bf16.bf16 {"
               "%0,%1,%2,%3,%4,%5,%6,%7,%8,%9,%10,%11,%12,%13,%14,%15,%16,%17,%18,%19,%20,%21,%22,%23,%24,%25,%26,%27,%28,%29,%30,%31,"
               "%32,%33,%34,%35,%36,%37,%38,%39,%40,%41,%42,%43,%44,%45,%46,%47,%48,%49,%50,%51,%52,%53,%54,%55,%56,%57,%58,%59,%60,%61,%62,%63"
               "}, %64, %65, 1, 1, 1, %66, 1;"
               : F16(d, 0), F16(d, 16), F16(d, 32), F16(d, 48) : "l"(a), "l"(b), "n"(TA));
}

__device__ __forceinline__ float bfr(float x) { return __bfloat162float(__float2bfloat16_rn(x)); }
__global__ void __launch_bounds__(256) ln_kernel(const bf16* __restrict__ x) {
  const int lane = threadIdx.x & 31, row = blockIdx.x * 8 + (threadIdx.x >> 5);
  {
    int i = blockIdx.x * 256 + threadIdx.x;
    if (i < 64) g_flag[i] = 0;
    for (int j = i; j < 20 * 4096; j += 256 * 256) g_part[j] = make_float4(0.f, 0.f, 0.f, 0.f);
    for (; i < NSEG * ACC_CHUNKS; i += 256 * 256) g_acc[i] = make_float4(0.f, 0.f, 0.f, 0.f);
  }
  const uint2* src = reinterpret_cast<const uint2*>(x + (size_t)row * DM);
  float v[20];
#pragma unroll
  for (int i = 0; i < 5; i++) {
    uint2 u = __ldg(src + i * 32 + lane);
    v[4 * i + 0] = __uint_as_float(u.x << 16); v[4 * i + 1] = __uint_as_float(u.x & 0xffff0000u);
    v[4 * i + 2] = __uint_as_float(u.y << 16); v[4 * i + 3] = __uint_as_float(u.y & 0xffff0000u);
  }
  float s = 0.f;
#pragma unroll
  for (int i = 0; i < 20; i++) s += v[i];
#pragma unroll
  for (int o = 16; o; o >>= 1) s += __shfl_xor_sync(~0u, s, o);
  const float mean = s * (1.0f / DM);
  float q = 0.f;
#pragma unroll
  for (int i = 0; i < 20; i++) { float d = v[i] - mean; q += d * d; }
#pragma unroll
  for (int o = 16; o; o >>= 1) q += __shfl_xor_sync(~0u, q, o);
  const float mb = bfr(mean), sd = bfr(sqrtf(bfr(bfr(q * (1.0f / DM)) + 1e-5f)));
  uint2* dst = reinterpret_cast<uint2*>(g_xn + (size_t)row * DM);
#pragma unroll
  for (int i = 0; i < 5; i++) {
    uint2 u;
    u.x = pack2(bfr(v[4 * i + 0] - mb) / sd, bfr(v[4 * i + 1] - mb) / sd);
    u.y = pack2(bfr(v[4 * i + 2] - mb) / sd, bfr(v[4 * i + 3] - mb) / sd);
    dst[i * 32 + lane] = u;
  }
}

namespace ck {
constexpr int CL = 6, NCL = 16, NRF = 8, NSS = 40 - NRF, NTP = 2;
constexpr uint32_t OFF_H = 0, OFF_WV = 51200, OFF_WO = OFF_WV + NSS * 2048, OFF_Q = OFF_WO + 86016, OFF_K = OFF_Q + 5120,
                   OFF_OG = OFF_K + 5120, OFF_RA = OFF_OG + 6144, OFF_P = OFF_RA + 3840, OFF_RT = OFF_P + 3200,
                   OFF_BAR = OFF_RT + 5120, SMEM = OFF_BAR + 128;
constexpr uint32_t B_X = 0, B_A = 8, B_T = 16, B_W = 24, B_WR = 32, B_B = 40  , B_XF = 88, B_DUMMY = 96;
enum { NB_M = 1, NB_QK = 2, NB_PM = 3, NB_V = 4, NB_TS = 5, NB_P = 6, NB_G = 7, NB_R = 8  , NB_S = 12, NB_V2 = 13, NB_M1 = 14, NB_O = 15 };
static_assert(SMEM <= 232448, "smem");
static_assert(OFF_WO % 1024 == 0 && OFF_Q % 1024 == 0, "align");
}
__device__ __forceinline__ uint32_t opq(uint32_t x) { asm volatile("" : "+r"(x)); return x; }

__device__ __forceinline__ uint32_t memrow_addr(uint32_t sb, uint32_t col0, uint32_t m) {
  return sb + ck::OFF_H + (col0 >> 6) * 5120 + 4096 + m * 128 + ((((col0 >> 3) & 7) ^ m) << 4);
}
struct MemLoad { float4 c[4]; };
__device__ __forceinline__ void memload_issue(MemLoad& m, int s, uint32_t warp, uint32_t lane) {
  const float4* p = g_acc + (s * ACC_CHUNKS + warp * 128) + lane;
#pragma unroll
  for (int q = 0; q < 4; q++) m.c[q] = ld_relaxed4(p + q * 32);
}
__device__ __forceinline__ void memload_finish(MemLoad& m, int s, uint32_t warp, uint32_t lane, uint32_t sb) {
  const float full = (float)ck::NCL;
  const uint32_t a4 = memrow_addr(sb, warp * 48 + (lane >> 3) * 8, lane & 7);
  const uint32_t a2 = memrow_addr(sb, warp * 48 + 32 + ((lane >> 3) & 1) * 8, lane & 7);
  int n = 0;
  while (true) {
    bool ok = m.c[0].w == full && m.c[1].w == full && m.c[2].w == full && m.c[3].w == full;
    if (__all_sync(~0u, ok)) break;
    if (++n > SPIN_LIMIT) __trap();
    memload_issue(m, s, warp, lane);
  }
  stsm4t(a4, pack2(m.c[0].x, m.c[1].x), pack2(m.c[2].x, m.c[3].x), pack2(m.c[0].y, m.c[1].y), pack2(m.c[2].y, m.c[3].y));
  stsm2t(a2, pack2(m.c[0].z, m.c[1].z), pack2(m.c[2].z, m.c[3].z));
}
#define HAND 39
#define XW1 -1
#define XW2 0
#define HOFF(k) ((uint64_t)((((k) >> 2) * 5120 + ((k) & 3) * 32) >> 4))

template <bool LOADS>
__device__ __forceinline__ void token_qk(const uint32_t* a, int s, uint32_t sb, uint32_t warp, uint32_t lane0, uint32_t zero) {
  using namespace ck;
  const uint32_t bar = sb + OFF_BAR;
  float d[16];
  mbar_wait(bar + B_X, (s + 1) & 1);
  if (LOADS && warp >= 4) bar_sync(NB_O, 256);
  if (LOADS && warp != 0) PROF(0, 4);
  const uint32_t db = opq((uint32_t)mkdesc(sb + OFF_H, 16, 1024, 1));
  WG_FENCE();
  wg_rs32x<0>(d, a[0], a[1], a[2], a[3], db);
#pragma unroll
  for (int k = 1; k < 40; k++) {
    wg_rs32x<1>(d, a[4 * k], a[4 * k + 1], a[4 * k + 2], a[4 * k + 3], db + (uint32_t)HOFF(k));
    if (LOADS && k == HAND)
      asm volatile("{\n.reg .pred p;\nsetp.lt.u32 p, %0, 4;\n@p bar.arrive %1, 256;\n}" :: "r"(warp), "n"((int)NB_O) : "memory");
  }
  WG_COMMIT();
  const uint32_t lane = opq(lane0), wg = warp >> 2, w4 = warp & 3;
  const uint32_t mat = lane >> 3, i = lane & 7, h = mat & 1, j0 = mat >> 1;
  const uint32_t ep0 = sb + OFF_Q + wg * 5120 + (8 * j0 + i) * 128 + (((2 * w4 + h) ^ i) << 4), ep1 = ep0 + 2048;
  WG_WAIT(0);
  if (LOADS) PROF(0, 5);
  if (!LOADS) bar_sync(NB_TS, 384);
  stsm4t(ep0, pack2(d[0], d[1]), pack2(d[2], d[3]), pack2(d[4], d[5]), pack2(d[6], d[7]));
  stsm4t(ep1, pack2(d[8], d[9]), pack2(d[10], d[11]), pack2(d[12], d[13]), pack2(d[14], d[15]));
  if (LOADS) PROF(0, 6);
  if (LOADS && warp < 4) {
    MemLoad m0, m1;
    memload_issue(m0, s, warp, lane);
    memload_issue(m1, s, warp + 4, lane);
    memload_finish(m0, s, warp, lane, sb);
    memload_finish(m1, s, warp + 4, lane, sb);
  }
  if (LOADS) PROF(0, 7);
}

__global__ void __launch_bounds__(384, 1)
chain_kernel(const __grid_constant__ CUtensorMap tm_x, const __grid_constant__ CUtensorMap tm_wv, const __grid_constant__ CUtensorMap tm_wo,
             const bf16* __restrict__ Wq, const bf16* __restrict__ Wk, const bf16* __restrict__ mem0, uint32_t zero) {
  using namespace ck;
  extern __shared__ __align__(1024) unsigned char smem[];
  const uint32_t sb = smem_u32(smem);
  const uint32_t tid0 = threadIdx.x;
  const uint32_t warp = __shfl_sync(~0u, threadIdx.x >> 5, 0);
  const int rank = blockIdx.x % CL, cluster = blockIdx.x / CL;
  const int hb = (rank / 3) * 3, j3 = rank % 3;
  const uint32_t bar = sb + OFF_BAR;

  if (tid0 == 0) {
    const int ntile = rank < 4 ? 7 : 6;
    mbar_init(bar + B_X, 1); mbar_init(bar + B_A, 1); mbar_init(bar + B_T, 1); mbar_init(bar + B_W, 1); mbar_init(bar + B_WR, 1);
    for (int i = 0; i < 3; i++) mbar_init(bar + B_B + 8 * i, 1);
    mbar_init(bar + B_XF, 1);
    asm volatile("fence.mbarrier_init.release.cluster;" ::: "memory");
    mbar_expect(bar + B_A, 2 * 1280); mbar_expect(bar + B_T, 2 * 2560);
    for (int i = 0; i < 3; i++) mbar_expect(bar + B_B + 8 * i, 2048);
    mbar_expect(bar + B_XF, CL * 4);
    mbar_expect(bar + B_X, 40960);
    for (int c = 0; c < 10; c++) tma2d(sb + OFF_H + c * 5120, &tm_x, c * 64, 0, bar + B_X);
    mbar_expect(bar + B_WR, NRF * 2048);
    tma2d(sb + OFF_Q, &tm_wv, blockIdx.x * 64, NSS * 16, bar + B_WR);
    mbar_expect(bar + B_W, NSS * 2048 + ntile * 12288);
    for (int i = 0; i < NSS / 8; i++) tma2d(sb + OFF_WV + i * 16384, &tm_wv, blockIdx.x * 64, i * 128, bar + B_W);
    for (int i = 0; i < ntile; i++) {
      const int col = i < 6 ? rank * 96 + i * 16 : 576 + rank * 16;
      for (int d = 0; d < CL; d++)
        tma2d(sb + OFF_WO + i * 12288 + d * 2048, &tm_wo, col, cluster * 384 + ((rank + CL - d) % CL) * 64, bar + B_W);
    }
  }
  asm volatile("griddepcontrol.launch_dependents;");
  for (int i = tid0; i < 640; i += 384) {
    const int m = i / 80, c = i % 80;
    sts4u(memrow_addr(sb, c * 8, m), __ldg(reinterpret_cast<const uint4*>(mem0) + i));
  }
  fence_async();
  __syncthreads();
  cluster_sync();

  if (warp < 8) {
    asm volatile("setmaxnreg.inc.sync.aligned.u32 208;");
    const uint32_t lane0 = __shfl_sync(~0u, opq(threadIdx.x & 31), threadIdx.x & 31);
    uint32_t a[160];
    {
      const uint32_t lane = tid0 & 31;
      const uint32_t* W = reinterpret_cast<const uint32_t*>((tid0 < 128 ? Wq : Wk) + (size_t)(2 * (lane & 3)) * HD + blockIdx.x * 64 + ((tid0 >> 5) & 3) * 16 + 2 * (lane >> 2));
#pragma unroll
      for (int k = 0; k < 40; k++) {
        a[4 * k + 0] = __ldg(W + (size_t)(16 * k + 0) * (HD / 2));
        a[4 * k + 1] = __ldg(W + (size_t)(16 * k + 1) * (HD / 2));
        a[4 * k + 2] = __ldg(W + (size_t)(16 * k + 8) * (HD / 2));
        a[4 * k + 3] = __ldg(W + (size_t)(16 * k + 9) * (HD / 2));
      }
#pragma unroll
      for (int k = 0; k < 80; k++) {
        const uint32_t w0 = a[2 * k], w1 = a[2 * k + 1];
        a[2 * k] = __byte_perm(w0, w1, 0x5410);
        a[2 * k + 1] = __byte_perm(w0, w1, 0x7632);
      }
    }
    token_qk<false>(a, -1, sb, warp, lane0, zero);
    mbar_wait(bar + B_W, 0);
    const float sc = 0.07216878364870322f * 1.4426950408889634f;

    for (int s = 0;; s++) {
      uint32_t lane;
      {
        const uint32_t ln = opq(lane0);
        const uint32_t x0 = sb + OFF_H + 4096 + (ln & 7) * 128 + (((ln >> 3) ^ (ln & 7)) << 4), x1 = x0 ^ 64;
        float c[16];
#pragma unroll
        for (int i = 0; i < 16; i++) c[i] = 0.f;
        uint32_t bf[1][16];
        bar_sync(NB_M1, 256);
        PROF(0, 0);
#pragma unroll
        for (int k = 0; k < 40; k += 2) {
          if (k == 24) bar_sync(NB_M, 384);
          uint32_t* b = bf[0] + 12;
          ldsm4(b[0], b[1], b[2], b[3], ((k & 2) ? x1 : x0) + (k >> 2) * 5120);
          float* d = c + ((k & 2) ? 8 : 0);
          mma16816(d, a[4 * k], a[4 * k + 1], a[4 * k + 2], a[4 * k + 3], b[0], b[1]);
          mma16816(d + 4, a[4 * k + 4], a[4 * k + 5], a[4 * k + 6], a[4 * k + 7], b[2], b[3]);
        }
#pragma unroll
        for (int i = 0; i < 4; i++) c[i] = (c[i] + c[4 + i]) + (c[8 + i] + c[12 + i]);
        asm volatile("add.u32 %0, %1, %2;" : "=r"(lane) : "r"(lane0), "r"(bf[0][15] & zero));
        const uint32_t qst = sb + OFF_Q + (warp >> 2) * 5120 + (32 + (lane & 7)) * 128 + (((2 * (warp & 3) + ((lane >> 3) & 1)) ^ (lane & 7)) << 4);
        stsm2t(qst, pack2(c[0], c[1]), pack2(c[2], c[3]));
        PROF(0, 1);
      }
      const uint32_t l7 = lane & 7, l3 = lane >> 3;
      const uint32_t sw0 = l7 * 128 + ((l3 ^ l7) << 4), sw1 = sw0 ^ 64;
      if (s == NSEG - 1) { fence_async(); bar_arrive(NB_S, 384); break; }
      if (warp < 5) {
        uint32_t qa[8], kb[8];
        const uint32_t kr = sb + OFF_K + warp * 1024, qr = sb + OFF_Q + 4096;
        ldsm4(kb[0], kb[1], kb[2], kb[3], kr + sw0); ldsm4(kb[4], kb[5], kb[6], kb[7], kr + sw1);
        const uint32_t off = OFF_RA + j3 * 1280 + warp * 256 + lane * 8;
        const uint32_t r1 = opq(mapa(sb, hb + (j3 + 1) % 3) + off), r2 = opq(mapa(sb, hb + (j3 + 2) % 3) + off);
        const uint32_t m1 = opq(mapa(bar + B_A, hb + (j3 + 1) % 3)), m2 = opq(mapa(bar + B_A, hb + (j3 + 2) % 3));
        fence_async();
        bar_sync(NB_QK, 256);
        ldsm4(qa[0], qa[1], qa[2], qa[3], qr + sw0);
        ldsm4(qa[4], qa[5], qa[6], qa[7], qr + sw1);
        if (warp == 4) { ldsm4(kb[0], kb[1], kb[2], kb[3], kr + sw0); ldsm4(kb[4], kb[5], kb[6], kb[7], kr + sw1); }
        float s0[4] = {0.f, 0.f, 0.f, 0.f}, s1[4] = {0.f, 0.f, 0.f, 0.f};
        mma16816(s0, qa[0], 0u, qa[1], 0u, kb[0], kb[1]);
        mma16816(s1, qa[2], 0u, qa[3], 0u, kb[2], kb[3]);
        mma16816(s0, qa[4], 0u, qa[5], 0u, kb[4], kb[5]);
        mma16816(s1, qa[6], 0u, qa[7], 0u, kb[6], kb[7]);
        const float x = s0[0] + s1[0], y = s0[1] + s1[1];
        st_async2(r1, __float_as_uint(x), __float_as_uint(y), m1);
        st_async2(r2, __float_as_uint(x), __float_as_uint(y), m2);
        sts2f(sb + off, x, y);
        PROF(0, 2);
      } else {
        bar_arrive(NB_QK, 256);
      }
      if (warp == 0) {
        bar_sync(NB_S, 384);
        const uint32_t ra = sb + OFF_RA + lane * 8;
        mbar_wait(bar + B_A, s & 1);
        PROF(0, 3);
        float p[10];
#pragma unroll
        for (int i = 0; i < 5; i++) {
          const float2 x = lds2f(ra + i * 256), y = lds2f(ra + i * 256 + 1280), z = lds2f(ra + i * 256 + 2560);
          p[2 * i] = (x.x + y.x) + z.x; p[2 * i + 1] = (x.y + y.y) + z.y;
        }
        float mx = fmaxf(fmaxf(fmaxf(p[0], p[1]), fmaxf(p[2], p[3])), fmaxf(fmaxf(p[4], p[5]), fmaxf(p[6], p[7])));
        mx = fmaxf(mx, fmaxf(p[8], p[9]));
        mx = fmaxf(mx, __shfl_xor_sync(~0u, mx, 1)); mx = fmaxf(mx, __shfl_xor_sync(~0u, mx, 2));
#pragma unroll
        for (int i = 0; i < 10; i++) p[i] = ex2(fmaf(p[i], sc, -mx * sc));
        sts4u(sb + OFF_P + lane * 16, make_uint4(pack2(p[0], p[1]), pack2(p[2], p[3]), pack2(p[4], p[5]), pack2(p[6], p[7])));
        sts1u(sb + OFF_P + 512 + lane * 4, pack2(p[8], p[9]));
        bar_arrive(NB_PM, 160);
        if (lane == 0) mbar_expect(bar + B_A, 2 * 1280);
        PROF(0, 4);
      } else if (warp < 5) {
        bar_arrive(NB_S, 384);
        const uint32_t rb = mapa(sb, lane < CL ? lane : 0);
        bar_sync(NB_V2, 256);
        if (warp == 1 && lane < CL) st_async1(rb + OFF_BAR + B_DUMMY, 0u, rb + OFF_BAR + B_XF);
      }
      {
        const uint32_t grp = warp >> 2, kq = warp & 3;
        const uint32_t wo = sb + OFF_WO + grp * 36864 + kq * 512 + ((l3 >> 1) * 8 + l7) * 32 + (((l3 & 1) ^ (kq >> 1) ^ (l7 >> 2)) << 4);
        const uint32_t og = sb + OFF_OG + kq * 256 + (lane ^ ((kq & 1) << 2)) * 8;
        float v[12];
#pragma unroll
        for (int i = 0; i < 12; i++) v[i] = 0.f;
        uint32_t f[2][12];
#pragma unroll
        for (int i = 0; i < 3; i++) ldsm4t(f[0][4 * i], f[0][4 * i + 1], f[0][4 * i + 2], f[0][4 * i + 3], wo + i * 12288);
#pragma unroll
        for (int i = 0; i < 3; i++) ldsm4t(f[1][4 * i], f[1][4 * i + 1], f[1][4 * i + 2], f[1][4 * i + 3], wo + i * 12288 + 2048);
        if (warp >= 5) {
          fence_async();
          bar_arrive(NB_S, 384);
        }
        bar_sync(NB_TS, 384);
#pragma unroll
        for (int u = 0; u < 3; u++) {
          mbar_wait(bar + B_B + 8 * u, s & 1);
          if (u == 0) PROF(0, 2);
          const float2 o0 = lds2f(og + u * 2048), o1 = lds2f(og + u * 2048 + 1024);
#pragma unroll
          for (int h = 0; h < 2; h++) {
            uint32_t* ff = f[h];
#pragma unroll
            for (int i = 0; i < 3; i++)
              mma16816(v + 4 * i, ff[4 * i], ff[4 * i + 1], ff[4 * i + 2], ff[4 * i + 3], __float_as_uint(h ? o1.x : o0.x), __float_as_uint(h ? o1.y : o0.y));
            if (u < 2) {
#pragma unroll
              for (int i = 0; i < 3; i++) ldsm4t(ff[4 * i], ff[4 * i + 1], ff[4 * i + 2], ff[4 * i + 3], wo + (2 * u + 2 + h) * 2048 + i * 12288);
            }
          }
        }
        const uint32_t xb = sb + OFF_Q + grp * 4608;
#pragma unroll
        for (int i = 1; i < 4; i++) {
          const uint32_t x = xb + ((i ^ kq) * 3 + (i - 1)) * 384;
          sts2f(x + lane * 8, v[i], v[4 + i]); sts1f(x + 256 + lane * 4, v[8 + i]);
        }
        float4* o = g_acc + (s * ACC_CHUNKS + (2 * rank + grp) * 128 + kq * 32) + lane;
        const uint32_t y = xb + kq * 1152;
        bar_sync(NB_R + grp, 128);
        const float2 p0 = lds2f(y + lane * 8), p1 = lds2f(y + 384 + lane * 8), p2 = lds2f(y + 768 + lane * 8);
        const float q0 = lds1f(y + 256 + lane * 4), q1 = lds1f(y + 640 + lane * 4), q2 = lds1f(y + 1024 + lane * 4);
        red4(o, (v[0] + p0.x) + (p1.x + p2.x), (v[4] + p0.y) + (p1.y + p2.y), (v[8] + q0) + (q1 + q2), 1.0f);
        if (warp) PROF(0, 3);
      }
      bar_sync(NB_G, 384);
      token_qk<true>(a, s, sb, warp, lane0, zero);
    }
    cluster_sync();
  } else {
    asm volatile("setmaxnreg.dec.sync.aligned.u32 88;");
    const uint32_t lane0 = __shfl_xor_sync(~0u, opq((threadIdx.x & 31) ^ 1), 1);
    uint32_t wv[4 * NRF];
    mbar_wait(bar + B_WR, 0);
    {
      const uint32_t l7 = tid0 & 7, l3 = (tid0 >> 3) & 3, w4 = (tid0 >> 5) & 3;
#pragma unroll
      for (int k = 0; k < NRF; k++)
        ldsm4t(wv[4 * k], wv[4 * k + 1], wv[4 * k + 2], wv[4 * k + 3], sb + OFF_Q + k * 2048 + ((l3 >> 1) * 8 + l7) * 128 + (((2 * w4 + (l3 & 1)) ^ l7) << 4));
    }
    bar_arrive(NB_TS, 384);
    mbar_wait(bar + B_W, 0);
    const float sc = 0.07216878364870322f * 1.4426950408889634f;

    bar_arrive(NB_M, 384);
    for (int s = 0; s < NSEG; s++) {
      const bool last = s == NSEG - 1;
      uint32_t va[10];
      {
        uint32_t wt_[4 * NTP];
        {
          const uint32_t ln = opq(lane0), l7 = ln & 7, l3 = ln >> 3;
#pragma unroll
          for (int k = 0; k < NTP; k++)
            ldsm4t(wt_[4 * k], wt_[4 * k + 1], wt_[4 * k + 2], wt_[4 * k + 3],
                   sb + OFF_WV + (NSS - NTP + k) * 2048 + ((l3 >> 1) * 8 + l7) * 128 + (((2 * (warp - 8) + (l3 & 1)) ^ l7) << 4));
        }
        mbar_wait(bar + B_X, s & 1);
        float v[20];
        uint64_t db = mkdesc(sb + OFF_H, 16, 1024, 1), da = mkdesc(sb + OFF_WV, 1024, 1024, 1);
        OPAQUE64(db); OPAQUE64(da);
        PROF(2, 0);
        bar_sync(NB_S, 384);
        WG_FENCE();
        wg_ss40<0, 1>(v, da, db);
#pragma unroll
        for (int k = 1; k < NSS - NTP; k++) wg_ss40<1, 1>(v, da + (uint64_t)(k * 128), db + HOFF(k));
#pragma unroll
        for (int k = 0; k < NTP; k++) wg_rs40<1>(v, wt_[4 * k], wt_[4 * k + 1], wt_[4 * k + 2], wt_[4 * k + 3], db + HOFF(NSS - NTP + k));
#pragma unroll
        for (int k = NSS; k < 40; k++) wg_rs40<1>(v, wv[4 * (k - NSS)], wv[4 * (k - NSS) + 1], wv[4 * (k - NSS) + 2], wv[4 * (k - NSS) + 3], db + HOFF(k));
        WG_COMMIT();
        WG_WAIT(0);
#pragma unroll
        for (int i = 0; i < 10; i++) va[i] = pack2(v[2 * i], v[2 * i + 1]);
      }
      PROF(2, 1);
      const uint32_t lane = opq(lane0), w4 = warp - 8, wt = w4 * 32 + lane;
      if (!last) {
        bar_arrive(NB_V2, 256);
        uint32_t da_[CL], db_[CL];
#pragma unroll
        for (int d = 0; d < CL; d++) {
          int r = rank + d; if (r >= CL) r -= CL;
          const uint32_t rb = mapa(sb, r);
          da_[d] = opq(rb + OFF_OG + wt * 8 + d * 1024); db_[d] = opq(rb + OFF_BAR + B_B + 8 * (d >> 1));
        }
        bar_sync(NB_PM, 160);
        const uint4 pa = lds4u(sb + OFF_P + lane * 16);
        const uint32_t pb = __float_as_uint(lds1f(sb + OFF_P + 512 + lane * 4));
        float o0[4] = {0.f, 0.f, 0.f, 0.f}, o1[4] = {0.f, 0.f, 0.f, 0.f}, o2[4] = {0.f, 0.f, 0.f, 0.f}, o3[4] = {0.f, 0.f, 0.f, 0.f};
        float os[4] = {0.f, 0.f, 0.f, 0.f};
        mma16816(os, pa.x, pa.z, pa.y, pa.w, 0x3f803f80u, 0x3f803f80u);
        mma16816(o0, pa.x, 0u, pa.y, 0u, va[0], va[2]);
        mma16816(o1, pa.x, 0u, pa.y, 0u, va[1], va[3]);
        mma16816(o2, pa.z, 0u, pa.w, 0u, va[4], va[6]);
        mma16816(os, pb, 0u, 0u, 0u, 0x3f803f80u, 0u);
        mma16816(o3, pa.z, 0u, pa.w, 0u, va[5], va[7]);
        mma16816(o0, pb, 0u, 0u, 0u, va[8], 0u);
        mma16816(o1, pb, 0u, 0u, 0u, va[9], 0u);
        const float inv = rcp(os[0] + os[2]);
        const uint32_t x = pack2((o0[0] + o2[0]) * inv, (o0[1] + o2[1]) * inv), y = pack2((o1[0] + o3[0]) * inv, (o1[1] + o3[1]) * inv);
#pragma unroll
        for (int d = 0; d < CL; d++) st_async2(da_[d], x, y, db_[d]);
        PROF(2, 3);
      }
      uint32_t e[5];
      {
        float v[20];
        uint64_t da = mkdesc(sb + OFF_Q, 16, 512, 1), db = mkdesc(sb + OFF_K, 16, 1024, 1);
        OPAQUE64(db); OPAQUE64(da);
        WG_FENCE();
        wg_ss40<0, 0>(v, da, db);
        wg_ss40<1, 0>(v, da + 2, db + 2);
        wg_ss40<1, 0>(v, da + 4, db + 4);
        wg_ss40<1, 0>(v, da + 6, db + 6);
        WG_COMMIT();
        WG_WAIT(0);
#pragma unroll
        for (int i = 0; i < 5; i++) e[i] = pack2(v[4 * i], v[4 * i + 1]);
      }
      if (!last) {
        bar_arrive(NB_TS, 384);
        if (w4 == 0) {
          if (lane == 0) { mbar_expect(bar + B_X, 40960); }
          mbar_wait(bar + B_XF, s & 1);
          if (lane == 0) mbar_expect(bar + B_XF, CL * 4);
          const int c2 = rank + 6 * lane;
          if (c2 < 10) tma2d_mc(sb + OFF_H + c2 * 5120, &tm_x, c2 * 64, (s + 1) * 32, bar + B_X, (uint16_t)0x3f);
          __syncwarp();
        } else if (w4 == 3) {
          if ((s & 3) == 0 && s > 0 && lane == 0) { __threadfence(); atomicAdd(&g_flag[(s >> 2) - 1], 1u); }
          __syncwarp();
        } else if (rank < 4) {
          const uint32_t kh = w4 - 1, l7 = lane & 7, l3 = lane >> 3;
          const uint32_t wo = sb + OFF_WO + 6 * 12288 + kh * 2048 + ((l3 >> 1) * 8 + l7) * 32 + (((l3 & 1) ^ (l7 >> 2)) << 4);
          const uint32_t og = sb + OFF_OG + kh * 1024 + lane * 8;
          float u[4] = {0.f, 0.f, 0.f, 0.f};
#pragma unroll
          for (int it = 0; it < 3; it++) {
            uint32_t ff[16];
#pragma unroll
            for (int kk = 0; kk < 4; kk++) ldsm4t(ff[4 * kk], ff[4 * kk + 1], ff[4 * kk + 2], ff[4 * kk + 3], wo + it * 4096 + kk * 512);
            mbar_wait(bar + B_B + 8 * it, s & 1);
#pragma unroll
            for (int kk = 0; kk < 4; kk++) {
              const float2 o = lds2f(og + it * 2048 + kk * 256);
              mma16816(u, ff[4 * kk], ff[4 * kk + 1], ff[4 * kk + 2], ff[4 * kk + 3], __float_as_uint(o.x), __float_as_uint(o.y));
            }
          }
          const uint32_t xb = sb + OFF_RA + lane * 8;
          sts2f(xb + kh * 256, kh ? u[0] : u[2], kh ? u[1] : u[3]);
          float4* o = g_acc + (s * ACC_CHUNKS + 1536 + rank * 64 + kh * 32) + lane;
          bar_sync(NB_R + 2, 64);
          const float2 x = lds2f(xb + 256 - kh * 256);
          red4(o, (kh ? u[2] : u[0]) + x.x, (kh ? u[3] : u[1]) + x.y, 0.f, 1.0f);
        }
        bar_sync(NB_G, 384);
        if (wt < 3) mbar_expect(bar + B_B + 8 * wt, 2048);
      }
      {
#pragma unroll
        for (int d = 1; d <= 2; d++) {
          const uint32_t rb = mapa(sb, hb + (j3 + d) % 3);
          st_async4(rb + OFF_RT + (2 - d) * 2560 + wt * 16, e[0], e[1], e[2], e[3], rb + OFF_BAR + B_T);
          st_async1(rb + OFF_RT + (2 - d) * 2560 + 2048 + wt * 4, e[4], rb + OFF_BAR + B_T);
        }
      }
      PROF(2, 4);
      mbar_wait(bar + B_T, s & 1);
      PROF(2, 5);
      float p[10];
#pragma unroll
      for (int i = 0; i < 5; i++) { p[2 * i] = __uint_as_float(e[i] << 16); p[2 * i + 1] = __uint_as_float(e[i] & 0xffff0000u); }
#pragma unroll
      for (int d = 0; d < 2; d++) {
        const uint4 x = lds4u(sb + OFF_RT + d * 2560 + wt * 16);
        const uint32_t y = __float_as_uint(lds1f(sb + OFF_RT + d * 2560 + 2048 + wt * 4));
        p[0] += __uint_as_float(x.x << 16); p[1] += __uint_as_float(x.x & 0xffff0000u);
        p[2] += __uint_as_float(x.y << 16); p[3] += __uint_as_float(x.y & 0xffff0000u);
        p[4] += __uint_as_float(x.z << 16); p[5] += __uint_as_float(x.z & 0xffff0000u);
        p[6] += __uint_as_float(x.w << 16); p[7] += __uint_as_float(x.w & 0xffff0000u);
        p[8] += __uint_as_float(y << 16); p[9] += __uint_as_float(y & 0xffff0000u);
      }
      if (wt == 0) mbar_expect(bar + B_T, 2 * 2560);
      PROF(2, 2);
      {
        const int tq = 8 * w4 + (lane >> 2) - 2 * (lane & 3);
        float mx = fmaxf(p[8], p[9]);
#pragma unroll
        for (int i = 0; i < 8; i++) { if (8 * (i >> 1) + (i & 1) > tq) p[i] = -INFINITY; mx = fmaxf(mx, p[i]); }
        mx = fmaxf(mx, __shfl_xor_sync(~0u, mx, 1)); mx = fmaxf(mx, __shfl_xor_sync(~0u, mx, 2));
        float sum = 0.f;
#pragma unroll
        for (int i = 0; i < 10; i++) { p[i] = ex2(fmaf(p[i], sc, -mx * sc)); sum += p[i]; }
        sum += __shfl_xor_sync(~0u, sum, 1); sum += __shfl_xor_sync(~0u, sum, 2);
        const float inv = rcp(sum);
        const uint32_t pr = sb + OFF_P + (lane >> 3) * 800 + w4 * 32 + (lane & 7) * 4;
#pragma unroll
        for (int i = 0; i < 5; i++) sts1u(pr + i * 128, pack2(p[2 * i] * inv, p[2 * i + 1] * inv));
        sts1u(pr + 640, 0u);
      }
      fence_async();
      if (!last) {
        {
          MemLoad ml;
          memload_issue(ml, s, warp, lane);
          const float4* px = g_acc + (s * ACC_CHUNKS + 1536 + w4 * 64) + lane;
          float4 x0 = ld_relaxed4(px), x1 = ld_relaxed4(px + 32);
          memload_finish(ml, s, warp, lane, sb);
          int n = 0;
          while (!__all_sync(~0u, x0.w == (float)NCL && x1.w == (float)NCL)) {
            if (++n > SPIN_LIMIT) __trap();
            x0 = ld_relaxed4(px); x1 = ld_relaxed4(px + 32);
          }
          stsm2t(memrow_addr(sb, 576 + w4 * 16 + ((lane >> 3) & 1) * 8, lane & 7), pack2(x0.x, x0.y + x0.z), pack2(x1.x, x1.y + x1.z));
        }
        bar_arrive(NB_M, 384);
      }
      PROF(2, 7);
      bar_sync(NB_P, 128);
      {
        float o[16];
        uint64_t db = mkdesc(sb + OFF_P, 128, 800, 0);
        OPAQUE64(db);
        uint32_t vb[10];
#pragma unroll
        for (int i = 0; i < 10; i++) asm volatile("add.u32 %0, %1, %2;" : "=r"(vb[i]) : "r"(va[i]), "r"(zero));
        WG_FENCE();
        wg_rs32<0>(o, vb[0], vb[1], vb[2], vb[3], db);
        wg_rs32<1>(o, vb[4], vb[5], vb[6], vb[7], db + 16);
        wg_rs32<1>(o, vb[8], vb[9], 0u, 0u, db + 32);
        WG_COMMIT();
        uint4* dst = reinterpret_cast<uint4*>(g_oT) + ((s * HD + blockIdx.x * 64 + w4 * 16) * 4 + lane);
        WG_WAIT(0);
        dst[0] = make_uint4(pack2(o[0], o[1]), pack2(o[4], o[5]), pack2(o[8], o[9]), pack2(o[12], o[13]));
        dst[32] = make_uint4(pack2(o[2], o[3]), pack2(o[6], o[7]), pack2(o[10], o[11]), pack2(o[14], o[15]));
      }
      fence_async();
      PROF(2, 6);
    }
    bar_sync(NB_P, 128);
    if (tid0 == 256) { __threadfence(); atomicAdd(&g_flag[15], 1u); }
    cluster_sync();
  }
}

namespace hk {
constexpr int STAGES = 4, STAGE = 49152, OFF_ST = STAGES * STAGE, OFF_BAR = OFF_ST + 32768, SMEM = OFF_BAR + 1024, NCTA = 36;
constexpr int N_G1 = 192, SB0 = 12  , N_FULL = 5 * SB0, N_ITEMS = N_G1 + 20 + N_FULL + 5 * (2 + 3 + 4 + 7);
struct Item { int type, mb, nt, k0, k1, nsplit; };
__device__ __forceinline__ Item get_item(int i) {
  Item t;
  if (i < N_G1) { t.type = 0; t.mb = i / 12; t.nt = i % 12; t.k0 = 0; t.k1 = 10; t.nsplit = 1; return t; }
  i -= N_G1; t.type = 1; t.nt = i % 5;
  if (i < 20) { t.mb = SB0 + i / 5; t.k0 = 0; t.k1 = 24; t.nsplit = t.mb == 15 ? 8 : t.mb - 9; return t; }
  i -= 20;
  if (i < N_FULL) { t.mb = i / 5; t.k0 = 0; t.k1 = 120; t.nsplit = 1; return t; }
  i -= N_FULL;
  int ns;
  if (i < 10) { t.mb = 12; ns = 2; } else if (i < 25) { i -= 10; t.mb = 13; ns = 3; } else if (i < 45) { i -= 25; t.mb = 14; ns = 4; } else { i -= 45; t.mb = 15; ns = 7; }
  const int p = i / 5;
  t.k0 = 24 + (96 * p) / ns; t.k1 = 24 + (96 * (p + 1)) / ns; t.nsplit = ns + 1;
  return t;
}
__device__ __forceinline__ void store_tile(const uint32_t* p, uint32_t stg, const CUtensorMap* tm, int c0, int r0, int wg, int t128) {
  const int lane = t128 & 31, r = (t128 >> 5) * 16 + (lane & 15);
  if (t128 == 0) asm volatile("cp.async.bulk.wait_group.read 0;" ::: "memory");
  bar_sync(1 + wg, 128);
#pragma unroll
  for (int j = 0; j < 8; j++) {
    const int c = 2 * j + (lane >> 4);
    const uint32_t a = stg + (c >> 3) * 8192 + r * 128 + (((c & 7) ^ (r & 7)) << 4);
    asm volatile("stmatrix.sync.aligned.m8n8.x4.shared.b16 [%0], {%1,%2,%3,%4};" :: "r"(a), "r"(p[4 * j]), "r"(p[4 * j + 1]), "r"(p[4 * j + 2]), "r"(p[4 * j + 3]) : "memory");
  }
  fence_async();
  bar_sync(1 + wg, 128);
  if (t128 == 0) {
    asm volatile("cp.async.bulk.tensor.2d.global.shared::cta.bulk_group [%0, {%2, %3}], [%1];" :: "l"(tm), "r"(stg), "r"(c0), "r"(r0) : "memory");
    asm volatile("cp.async.bulk.tensor.2d.global.shared::cta.bulk_group [%0, {%2, %3}], [%1];" :: "l"(tm), "r"(stg + 8192), "r"(c0 + 64), "r"(r0) : "memory");
    asm volatile("cp.async.bulk.commit_group;" ::: "memory");
  }
}
__device__ __forceinline__ void wait_flag(const unsigned* f, unsigned target) {
  unsigned v; int n = 0;
  while (true) {
    asm volatile("ld.acquire.gpu.global.u32 %0, [%1];" : "=r"(v) : "l"(f) : "memory");
    if (v >= target) break;
    if (++n > (1 << 22)) __trap();
    __nanosleep(200);
  }
  asm volatile("fence.proxy.async;" ::: "memory");
}
}
__global__ void __launch_bounds__(384, 1)
helper_kernel(const __grid_constant__ CUtensorMap tm_x, const __grid_constant__ CUtensorMap tm_g, const __grid_constant__ CUtensorMap tm_u,
              const __grid_constant__ CUtensorMap tm_h, const __grid_constant__ CUtensorMap tm_o, const __grid_constant__ CUtensorMap tm_wd,
              const __grid_constant__ CUtensorMap tm_wo, const __grid_constant__ CUtensorMap tm_hs, const __grid_constant__ CUtensorMap tm_out,
              const bf16* __restrict__ x) {
  using namespace hk;
  extern __shared__ __align__(1024) unsigned char smem[];
  const uint32_t sb = smem_u32(smem), bar = sb + OFF_BAR;
  const int tid = threadIdx.x, lane = tid & 31, wg = __shfl_sync(~0u, tid >> 7, 0);
  if (tid == 0) { for (int i = 0; i < STAGES; i++) { mbar_init(bar + 8 * i, 1); mbar_init(bar + 64 + 8 * i, 2); } asm volatile("fence.mbarrier_init.release.cluster;" ::: "memory"); }
  __syncthreads();
  if (wg == 2) {
    asm volatile("setmaxnreg.dec.sync.aligned.u32 40;");
    if (tid == 256) {
      uint32_t it = 0;
      for (int i = blockIdx.x; i < N_ITEMS; i += NCTA) {
        const Item t = get_item(i);
        const int m0 = t.mb * 128, n0 = t.nt * 128;
        for (int kb = t.k0; kb < t.k1; kb++, it++) {
          const uint32_t st = it % STAGES, base = sb + st * STAGE, full = bar + 8 * st;
          if (t.type == 1 && kb == 0) wait_flag(&g_flag[16 + t.mb], 24);
          mbar_wait_long(bar + 64 + 8 * st, ((it / STAGES) & 1) ^ 1);
          if (t.type == 0) {
            mbar_expect(full, 49152);
            tma2d(base, &tm_x, kb * 64, m0, full);
            tma2d(base + 16384, &tm_g, n0, kb * 64, full);
            tma2d(base + 24576, &tm_g, n0 + 64, kb * 64, full);
            tma2d(base + 32768, &tm_u, n0, kb * 64, full);
            tma2d(base + 40960, &tm_u, n0 + 64, kb * 64, full);
          } else if (kb < 24) {
            mbar_expect(full, 32768);
            tma2d(base, &tm_h, kb * 64, m0, full);
            tma2d(base + 16384, &tm_wd, n0, kb * 64, full);
            tma2d(base + 24576, &tm_wd, n0 + 64, kb * 64, full);
          } else {
            const int k0 = (kb - 24) * 64;
            mbar_expect(full, 32768);
            tma2d(base + 16384, &tm_wo, n0, k0, full);
            tma2d(base + 24576, &tm_wo, n0 + 64, k0, full);
            if (kb == 24 || kb == t.k0) wait_flag(&g_flag[t.mb], 96);
            tma3d(base, &tm_o, 0, k0, m0 / 32, full);
          }
        }
      }
    }
  } else {
    asm volatile("setmaxnreg.inc.sync.aligned.u32 232;");
    uint32_t it = 0;
    for (int i = blockIdx.x; i < N_ITEMS; i += NCTA) {
      const Item t = get_item(i);
      const int row = t.mb * 128 + wg * 64 + ((tid >> 5) & 3) * 16 + (lane >> 2);
      HPROF(i, 0);
      if (t.type == 0) {
        float dg[64], du[64];
#pragma unroll
        for (int j = 0; j < 64; j++) { dg[j] = 0.f; du[j] = 0.f; }
        for (int kb = 0; kb < 10; kb++, it++) {
          const uint32_t st = it % STAGES, base = sb + st * STAGE;
          mbar_wait_long(bar + 8 * st, (it / STAGES) & 1);
          const uint64_t da = mkdesc(base + wg * 8192, 16, 1024, 1), db = mkdesc(base + 16384, 8192, 1024, 1);
          WG_FENCE();
#pragma unroll
          for (int k = 0; k < 4; k++) { wg_ss128<0>(dg, da + 2 * k, db + 128 * k); wg_ss128<0>(du, da + 2 * k, db + 1024 + 128 * k); }
          WG_COMMIT();
          WG_WAIT(1);
          if (kb > 0 && (tid & 127) == 0) mbar_arrive(bar + 64 + 8 * ((it - 1) % STAGES));
        }
        WG_WAIT(0);
        if ((tid & 127) == 0) mbar_arrive(bar + 64 + 8 * ((it - 1) % STAGES));
        uint32_t p[32];
#pragma unroll
        for (int j = 0; j < 32; j++) p[j] = pack2(bfr(dg[2 * j]) * bfr(du[2 * j]), bfr(dg[2 * j + 1]) * bfr(du[2 * j + 1]));
        store_tile(p, sb + OFF_ST + wg * 16384, &tm_hs, t.nt * 128, t.mb * 128 + wg * 64, wg, tid & 127);
        if ((tid & 127) == 0) {
          asm volatile("cp.async.bulk.wait_group 0;" ::: "memory");
          asm volatile("fence.proxy.async;" ::: "memory");
          __threadfence(); atomicAdd(&g_flag[16 + t.mb], 1u);
        }
      } else {
        float d[64];
#pragma unroll
        for (int j = 0; j < 64; j++) d[j] = 0.f;
        uint32_t xr[32];
        {
          const uint32_t* xi = reinterpret_cast<const uint32_t*>(x + (size_t)row * DM + t.nt * 128 + (lane & 3) * 2);
#pragma unroll
          for (int j = 0; j < 16; j++) { xr[2 * j] = __ldg(xi + j * 4); xr[2 * j + 1] = __ldg(xi + j * 4 + 4 * DM); }
        }
        int kb = t.k0;
        for (; kb < t.k1 && kb < 24; kb++, it++) {
          const uint32_t st = it % STAGES, base = sb + st * STAGE;
          mbar_wait_long(bar + 8 * st, (it / STAGES) & 1);
          const uint64_t da = mkdesc(base + wg * 8192, 16, 1024, 1), db = mkdesc(base + 16384, 8192, 1024, 1);
          WG_FENCE();
#pragma unroll
          for (int k = 0; k < 4; k++) wg_ss128<0>(d, da + 2 * k, db + 128 * k);
          WG_COMMIT();
          WG_WAIT(1);
          if (kb > t.k0 && (tid & 127) == 0) mbar_arrive(bar + 64 + 8 * ((it - 1) % STAGES));
        }
        WG_WAIT(0);
        for (; kb < t.k1; kb++, it++) {
          const uint32_t st = it % STAGES, base = sb + st * STAGE;
          mbar_wait_long(bar + 8 * st, (it / STAGES) & 1);
          if (kb == 24 || kb == t.k0) HPROF(i, 1);
          const uint64_t da = mkdesc(base + wg * 8192, 4096, 512, 2), db = mkdesc(base + 16384, 8192, 1024, 1);
          WG_FENCE();
#pragma unroll
          for (int k = 0; k < 4; k++) wg_ss128<1>(d, da + 64 * k, db + 128 * k);
          WG_COMMIT();
          WG_WAIT(1);
          if (kb > t.k0 && (tid & 127) == 0) mbar_arrive(bar + 64 + 8 * ((it - 1) % STAGES));
        }
        WG_WAIT(0);
        if ((tid & 127) == 0) mbar_arrive(bar + 64 + 8 * ((it - 1) % STAGES));
        HPROF(i, 2);
        {
          const uint32_t m = t.k0 == 0 ? 0xffff0000u : 0u;
#pragma unroll
          for (int j = 0; j < 32; j++) { d[2 * j] += __uint_as_float((xr[j] << 16) & m); d[2 * j + 1] += __uint_as_float(xr[j] & m); }
        }
        bool fin = true;
        if (t.nsplit > 1) {
          const int ti = (t.mb - SB0) * 5 + t.nt;
          float4* pp = g_part + ti * 4096 + tid;
#pragma unroll
          for (int j = 0; j < 16; j++) red4(pp + j * 256, d[4 * j], d[4 * j + 1], d[4 * j + 2], d[4 * j + 3]);
          __threadfence();
          bar_sync(1 + wg, 128);
          volatile unsigned* sflag = reinterpret_cast<volatile unsigned*>(smem + OFF_BAR + 256 + wg * 4);
          if ((tid & 127) == 0) {
            const unsigned old = atomicAdd(&g_flag[32 + ti], wg ? 0x10000u : 1u);
            *sflag = ((wg ? old >> 16 : old & 0xffffu) == (unsigned)t.nsplit - 1);
            __threadfence();
          }
          bar_sync(1 + wg, 128);
          fin = __shfl_sync(~0u, *sflag, 0) != 0;
          if (fin) {
#pragma unroll
            for (int j = 0; j < 16; j++) {
              const float4 u = __ldcg(pp + j * 256);
              d[4 * j] = u.x; d[4 * j + 1] = u.y; d[4 * j + 2] = u.z; d[4 * j + 3] = u.w;
            }
          }
        }
        if (fin) {
          uint32_t p[32];
#pragma unroll
          for (int j = 0; j < 32; j++) p[j] = pack2(d[2 * j], d[2 * j + 1]);
          store_tile(p, sb + OFF_ST + wg * 16384, &tm_out, t.nt * 128, t.mb * 128 + wg * 64, wg, tid & 127);
        }
      }
      HPROF(i, 3);
    }
    if ((tid & 127) == 0) asm volatile("cp.async.bulk.wait_group 0;" ::: "memory");
    asm volatile("griddepcontrol.wait;" ::: "memory");
  }
}

typedef CUresult (*EncodeFn)(CUtensorMap*, CUtensorMapDataType, cuuint32_t, void*, const cuuint64_t*, const cuuint64_t*, const cuuint32_t*,
                             const cuuint32_t*, CUtensorMapInterleave, CUtensorMapSwizzle, CUtensorMapL2promotion, CUtensorMapFloatOOBfill);
static void make_map(EncodeFn enc, CUtensorMap* m, const void* p, int rank, const cuuint64_t* dims, const cuuint64_t* strides,
                     const cuuint32_t* box, CUtensorMapSwizzle swz) {
  cuuint32_t es[3] = {1, 1, 1};
  enc(m, CU_TENSOR_MAP_DATA_TYPE_BFLOAT16, rank, const_cast<void*>(p), dims, strides, box, es, CU_TENSOR_MAP_INTERLEAVE_NONE, swz,
      CU_TENSOR_MAP_L2_PROMOTION_L2_128B, CU_TENSOR_MAP_FLOAT_OOB_FILL_NONE);
}
static void map2d(EncodeFn enc, CUtensorMap* m, const void* p, int cols, int rows, int bc, int br, CUtensorMapSwizzle swz) {
  cuuint64_t dims[2] = {(cuuint64_t)cols, (cuuint64_t)rows}, strides[1] = {(cuuint64_t)cols * 2};
  cuuint32_t box[2] = {(cuuint32_t)bc, (cuuint32_t)br};
  make_map(enc, m, p, 2, dims, strides, box, swz);
}

extern "C" void kernel_launch(void* const* d_in, const int* in_sizes, int n_in, void* d_out, int out_size) {
  const bf16* x = (const bf16*)d_in[0];
  const bf16* mem0 = (const bf16*)d_in[1];
  const bf16* Wq = (const bf16*)d_in[2];
  const bf16* Wk = (const bf16*)d_in[3];
  const bf16* Wv = (const bf16*)d_in[4];
  const bf16* Wo = (const bf16*)d_in[5];
  const bf16* Wg = (const bf16*)d_in[8];
  const bf16* Wu = (const bf16*)d_in[9];
  const bf16* Wd = (const bf16*)d_in[10];
  bf16* out = (bf16*)d_out;

  void* fn = nullptr; cudaDriverEntryPointQueryResult qr;
  cudaGetDriverEntryPoint("cuTensorMapEncodeTiled", &fn, cudaEnableDefault, &qr);
  EncodeFn enc = (EncodeFn)fn;
  void *p_xn, *p_oT, *p_h;
  cudaGetSymbolAddress(&p_xn, g_xn); cudaGetSymbolAddress(&p_oT, g_oT); cudaGetSymbolAddress(&p_h, g_h);

  CUtensorMap t_x32, t_wv, t_wo16, t_x128, t_wg, t_wu, t_h, t_o, t_wd, t_wo64, t_hs, t_out;
  map2d(enc, &t_hs, p_h, FF, SEQ, 64, 64, CU_TENSOR_MAP_SWIZZLE_128B);
  map2d(enc, &t_out, out, DM, SEQ, 64, 64, CU_TENSOR_MAP_SWIZZLE_128B);
  map2d(enc, &t_x32, p_xn, DM, SEQ, 64, 32, CU_TENSOR_MAP_SWIZZLE_128B);
  map2d(enc, &t_wv, Wv, HD, DM, 64, 128, CU_TENSOR_MAP_SWIZZLE_128B);
  map2d(enc, &t_wo16, Wo, DM, HD, 16, 64, CU_TENSOR_MAP_SWIZZLE_32B);
  map2d(enc, &t_x128, p_xn, DM, SEQ, 64, 128, CU_TENSOR_MAP_SWIZZLE_128B);
  map2d(enc, &t_wg, Wg, FF, DM, 64, 64, CU_TENSOR_MAP_SWIZZLE_128B);
  map2d(enc, &t_wu, Wu, FF, DM, 64, 64, CU_TENSOR_MAP_SWIZZLE_128B);
  map2d(enc, &t_h, p_h, FF, SEQ, 64, 128, CU_TENSOR_MAP_SWIZZLE_128B);
  map2d(enc, &t_wd, Wd, DM, FF, 64, 64, CU_TENSOR_MAP_SWIZZLE_128B);
  map2d(enc, &t_wo64, Wo, DM, HD, 64, 64, CU_TENSOR_MAP_SWIZZLE_128B);
  {
    cuuint64_t dims[3] = {32, (cuuint64_t)HD, (cuuint64_t)NSEG}, strides[2] = {64, (cuuint64_t)HD * 64};
    cuuint32_t box[3] = {32, 64, 4};
    make_map(enc, &t_o, p_oT, 3, dims, strides, box, CU_TENSOR_MAP_SWIZZLE_64B);
  }
  cudaFuncSetAttribute(chain_kernel, cudaFuncAttributeMaxDynamicSharedMemorySize, ck::SMEM + CK_EXTRA);
  cudaFuncSetAttribute(helper_kernel, cudaFuncAttributeMaxDynamicSharedMemorySize, hk::SMEM);

  cudaStream_t st = cudaStreamPerThread;
  ln_kernel<<<256, 256, 0, st>>>(x);
  {
    cudaLaunchConfig_t cfg = {};
    cfg.gridDim = dim3(ck::CL * ck::NCL); cfg.blockDim = dim3(384); cfg.dynamicSmemBytes = ck::SMEM + CK_EXTRA; cfg.stream = st;
    cudaLaunchAttribute at[1];
    at[0].id = cudaLaunchAttributeClusterDimension; at[0].val.clusterDim.x = ck::CL; at[0].val.clusterDim.y = 1; at[0].val.clusterDim.z = 1;
    cfg.attrs = at; cfg.numAttrs = 1;
    cudaLaunchKernelEx(&cfg, chain_kernel, t_x32, t_wv, t_wo16, Wq, Wk, mem0, 0u);
  }
  {
    cudaLaunchConfig_t cfg = {};
    cfg.gridDim = dim3(hk::NCTA); cfg.blockDim = dim3(384); cfg.dynamicSmemBytes = hk::SMEM; cfg.stream = st;
    cudaLaunchAttribute at[1];
    at[0].id = cudaLaunchAttributeProgrammaticStreamSerialization; at[0].val.programmaticStreamSerializationAllowed = 1;
    cfg.attrs = at; cfg.numAttrs = 1;
    cudaLaunchKernelEx(&cfg, helper_kernel, t_x128, t_wg, t_wu, t_h, t_o, t_wd, t_wo64, t_hs, t_out, x);
  }
}
```

```cpp
#include <cuda_runtime.h>
#include <cuda_bf16.h>
#include <cuda.h>
#include <stdint.h>

typedef __nv_bfloat16 bf16;

constexpr int SEQ = 2048, DM = 640, HD = 6144, FF = 1536, NSEG = 64;
constexpr int ACC_CHUNKS = 1920;

__device__ bf16 g_xn[SEQ * DM];
__device__ bf16 g_oT[NSEG * HD * 32];
__device__ bf16 g_h[SEQ * FF];
__device__ float4 g_acc[NSEG * ACC_CHUNKS];
__device__ float4 g_part[20 * 4096];
__device__ unsigned g_flag[64];
#define SPROF() do {} while (0)
#define CK_EXTRA 0
#define HPROF(i, k) do {} while (0)
#define PPROF(t, k) do {} while (0)
#define PROF(who, slot) do {} while (0)

__device__ __forceinline__ uint32_t smem_u32(const void* p) { return (uint32_t)__cvta_generic_to_shared(p); }
__device__ __forceinline__ uint32_t mapa(uint32_t a, uint32_t r) { uint32_t o; asm("mapa.shared::cluster.u32 %0, %1, %2;" : "=r"(o) : "r"(a), "r"(r)); return o; }
__device__ __forceinline__ void mbar_init(uint32_t b, int c) { asm volatile("mbarrier.init.shared::cta.b64 [%0], %1;" :: "r"(b), "r"(c) : "memory"); }
__device__ __forceinline__ void mbar_expect(uint32_t b, uint32_t bytes) { asm volatile("mbarrier.arrive.expect_tx.shared::cta.b64 _, [%0], %1;" :: "r"(b), "r"(bytes) : "memory"); }
__device__ __forceinline__ void mbar_arrive(uint32_t b) { asm volatile("mbarrier.arrive.shared::cta.b64 _, [%0];" :: "r"(b) : "memory"); }
constexpr int SPIN_LIMIT = 1 << 20;
__device__ __forceinline__ void mbar_wait(uint32_t b, uint32_t ph) {
  asm volatile("{\n.reg .pred p;\n.reg .u32 n;\nmov.u32 n, 0;\n"
               "W: mbarrier.try_wait.parity.shared::cta.b64 p, [%0], %1;\n@p bra D;\n"
               "add.u32 n, n, 1;\nsetp.lt.u32 p, n, 0x40000;\n@p bra W;\ntrap;\nD:\n}" :: "r"(b), "r"(ph) : "memory");
}
__device__ __forceinline__ void mbar_wait_long(uint32_t b, uint32_t ph) {
  asm volatile("{\n.reg .pred p;\n.reg .u32 n;\nmov.u32 n, 0;\n"
               "W: mbarrier.try_wait.parity.shared::cta.b64 p, [%0], %1;\n@p bra D;\n"
               "add.u32 n, n, 1;\nsetp.lt.u32 p, n, 0x400000;\n@p bra W;\ntrap;\nD:\n}" :: "r"(b), "r"(ph) : "memory");
}
__device__ __forceinline__ void bar_sync(int id, int n) { asm volatile("bar.sync %0, %1;" :: "r"(id), "r"(n) : "memory"); }
__device__ __forceinline__ void bar_arrive(int id, int n) { asm volatile("bar.arrive %0, %1;" :: "r"(id), "r"(n) : "memory"); }
__device__ __forceinline__ void fence_async() { asm volatile("fence.proxy.async.shared::cta;" ::: "memory"); }
__device__ __forceinline__ void cluster_sync() { asm volatile("barrier.cluster.arrive.release.aligned;\nbarrier.cluster.wait.acquire.aligned;" ::: "memory"); }
__device__ __forceinline__ void tma2d(uint32_t dst, const CUtensorMap* m, int c0, int c1, uint32_t bar) {
  asm volatile("cp.async.bulk.tensor.2d.shared::cluster.global.mbarrier::complete_tx::bytes [%0], [%1, {%3, %4}], [%2];"
               :: "r"(dst), "l"(m), "r"(bar), "r"(c0), "r"(c1) : "memory");
}
__device__ __forceinline__ void tma2d_mc(uint32_t dst, const CUtensorMap* m, int c0, int c1, uint32_t bar, uint16_t mask) {
  asm volatile("cp.async.bulk.tensor.2d.shared::cluster.global.mbarrier::complete_tx::bytes.multicast::cluster [%0], [%1, {%3, %4}], [%2], %5;"
               :: "r"(dst), "l"(m), "r"(bar), "r"(c0), "r"(c1), "h"(mask) : "memory");
}
__device__ __forceinline__ void tma3d(uint32_t dst, const CUtensorMap* m, int c0, int c1, int c2, uint32_t bar) {
  asm volatile("cp.async.bulk.tensor.3d.shared::cluster.global.mbarrier::complete_tx::bytes [%0], [%1, {%3, %4, %5}], [%2];"
               :: "r"(dst), "l"(m), "r"(bar), "r"(c0), "r"(c1), "r"(c2) : "memory");
}
__device__ __forceinline__ void st_async1(uint32_t a, uint32_t x, uint32_t mb) {
  asm volatile("st.async.weak.shared::cluster.mbarrier::complete_tx::bytes.b32 [%0], %1, [%2];" :: "r"(a), "r"(x), "r"(mb) : "memory");
}
__device__ __forceinline__ void st_async2(uint32_t a, uint32_t x, uint32_t y, uint32_t mb) {
  asm volatile("st.async.weak.shared::cluster.mbarrier::complete_tx::bytes.v2.b32 [%0], {%1,%2}, [%3];" :: "r"(a), "r"(x), "r"(y), "r"(mb) : "memory");
}
__device__ __forceinline__ void st_async4(uint32_t a, uint32_t x, uint32_t y, uint32_t z, uint32_t w, uint32_t mb) {
  asm volatile("st.async.weak.shared::cluster.mbarrier::complete_tx::bytes.v4.b32 [%0], {%1,%2,%3,%4}, [%5];" :: "r"(a), "r"(x), "r"(y), "r"(z), "r"(w), "r"(mb) : "memory");
}
__device__ __forceinline__ void ldsm4(uint32_t& r0, uint32_t& r1, uint32_t& r2, uint32_t& r3, uint32_t a) {
  asm volatile("ldmatrix.sync.aligned.m8n8.x4.shared.b16 {%0,%1,%2,%3}, [%4];" : "=r"(r0), "=r"(r1), "=r"(r2), "=r"(r3) : "r"(a) : "memory");
}
__device__ __forceinline__ void ldsm4t(uint32_t& r0, uint32_t& r1, uint32_t& r2, uint32_t& r3, uint32_t a) {
  asm volatile("ldmatrix.sync.aligned.m8n8.x4.trans.shared.b16 {%0,%1,%2,%3}, [%4];" : "=r"(r0), "=r"(r1), "=r"(r2), "=r"(r3) : "r"(a) : "memory");
}
__device__ __forceinline__ void stsm4t(uint32_t a, uint32_t r0, uint32_t r1, uint32_t r2, uint32_t r3) {
  asm volatile("stmatrix.sync.aligned.m8n8.x4.trans.shared.b16 [%0], {%1,%2,%3,%4};" :: "r"(a), "r"(r0), "r"(r1), "r"(r2), "r"(r3) : "memory");
}
__device__ __forceinline__ void stsm1t(uint32_t a, uint32_t r0) {
  asm volatile("stmatrix.sync.aligned.m8n8.x1.trans.shared.b16 [%0], {%1};" :: "r"(a), "r"(r0) : "memory");
}
__device__ __forceinline__ void stsm2t(uint32_t a, uint32_t r0, uint32_t r1) {
  asm volatile("stmatrix.sync.aligned.m8n8.x2.trans.shared.b16 [%0], {%1,%2};" :: "r"(a), "r"(r0), "r"(r1) : "memory");
}
__device__ __forceinline__ void mma16816(float* d, uint32_t a0, uint32_t a1, uint32_t a2, uint32_t a3, uint32_t b0, uint32_t b1) {
  asm volatile("mma.sync.aligned.m16n8k16.row.col.f32.bf16.bf16.f32 {%0,%1,%2,%3}, {%4,%5,%6,%7}, {%8,%9}, {%0,%1,%2,%3};"
               : "+f"(d[0]), "+f"(d[1]), "+f"(d[2]), "+f"(d[3]) : "r"(a0), "r"(a1), "r"(a2), "r"(a3), "r"(b0), "r"(b1));
}
__device__ __forceinline__ float ex2(float x) { float r; asm("ex2.approx.ftz.f32 %0, %1;" : "=f"(r) : "f"(x)); return r; }
__device__ __forceinline__ float rcp(float x) { float r; asm("rcp.approx.ftz.f32 %0, %1;" : "=f"(r) : "f"(x)); return r; }
__device__ __forceinline__ uint32_t pack2(float lo, float hi) { uint32_t r; asm("cvt.rn.bf16x2.f32 %0, %1, %2;" : "=r"(r) : "f"(hi), "f"(lo)); return r; }
__device__ __forceinline__ float2 lds2f(uint32_t a) { float2 v; asm volatile("ld.shared.v2.f32 {%0,%1}, [%2];" : "=f"(v.x), "=f"(v.y) : "r"(a) : "memory"); return v; }
__device__ __forceinline__ float4 lds4f(uint32_t a) { float4 v; asm volatile("ld.shared.v4.f32 {%0,%1,%2,%3}, [%4];" : "=f"(v.x), "=f"(v.y), "=f"(v.z), "=f"(v.w) : "r"(a) : "memory"); return v; }
__device__ __forceinline__ uint4 lds4u(uint32_t a) { uint4 v; asm volatile("ld.shared.v4.u32 {%0,%1,%2,%3}, [%4];" : "=r"(v.x), "=r"(v.y), "=r"(v.z), "=r"(v.w) : "r"(a) : "memory"); return v; }
__device__ __forceinline__ float lds1f(uint32_t a) { float v; asm volatile("ld.shared.f32 %0, [%1];" : "=f"(v) : "r"(a) : "memory"); return v; }
__device__ __forceinline__ void sts4f(uint32_t a, float x, float y, float z, float w) { asm volatile("st.shared.v4.f32 [%0], {%1,%2,%3,%4};" :: "r"(a), "f"(x), "f"(y), "f"(z), "f"(w) : "memory"); }
__device__ __forceinline__ void sts2f(uint32_t a, float x, float y) { asm volatile("st.shared.v2.f32 [%0], {%1,%2};" :: "r"(a), "f"(x), "f"(y) : "memory"); }
__device__ __forceinline__ void sts1f(uint32_t a, float x) { asm volatile("st.shared.f32 [%0], %1;" :: "r"(a), "f"(x) : "memory"); }
__device__ __forceinline__ void sts1u(uint32_t a, uint32_t x) { asm volatile("st.shared.u32 [%0], %1;" :: "r"(a), "r"(x) : "memory"); }
__device__ __forceinline__ void sts4u(uint32_t a, uint4 v) { asm volatile("st.shared.v4.u32 [%0], {%1,%2,%3,%4};" :: "r"(a), "r"(v.x), "r"(v.y), "r"(v.z), "r"(v.w) : "memory"); }
__device__ __forceinline__ float4 ld_relaxed4(const float4* p) {
  float4 r; asm volatile("ld.relaxed.gpu.global.v4.f32 {%0,%1,%2,%3}, [%4];" : "=f"(r.x), "=f"(r.y), "=f"(r.z), "=f"(r.w) : "l"(p) : "memory"); return r;
}
__device__ __forceinline__ void red4(float4* p, float a, float b, float c, float d) {
  asm volatile("red.relaxed.gpu.global.add.v4.f32 [%0], {%1,%2,%3,%4};" :: "l"(p), "f"(a), "f"(b), "f"(c), "f"(d) : "memory");
}
__device__ __forceinline__ uint64_t mkdesc(uint32_t addr, uint32_t lbo, uint32_t sbo, uint32_t swz) {
  return (uint64_t)((addr & 0x3FFFF) >> 4) | ((uint64_t)(lbo >> 4) << 16) | ((uint64_t)(sbo >> 4) << 32) | ((uint64_t)swz << 62);
}
#define WG_FENCE() asm volatile("wgmma.fence.sync.aligned;" ::: "memory")
#define WG_COMMIT() asm volatile("wgmma.commit_group.sync.aligned;" ::: "memory")
#define WG_WAIT(n) asm volatile("wgmma.wait_group.sync.aligned %0;" :: "n"(n) : "memory")
#define OPAQUE64(x) asm volatile("" : "+l"(x))

#define F4(d, i) "+f"(d[i]), "+f"(d[i + 1]), "+f"(d[i + 2]), "+f"(d[i + 3])
#define F16(d, i) F4(d, i), F4(d, i + 4), F4(d, i + 8), F4(d, i + 12)
template <int ACC>
__device__ __forceinline__ void wg_rs32(float* d, uint32_t a0, uint32_t a1, uint32_t a2, uint32_t a3, uint64_t b) {
  asm volatile("wgmma.mma_async.sync.aligned.m64n32k16.f32.bf16.bf16 {%0,%1,%2,%3,%4,%5,%6,%7,%8,%9,%10,%11,%12,%13,%14,%15}, {%16,%17,%18,%19}, %20, %21, 1, 1, 0;"
               : F16(d, 0) : "r"(a0), "r"(a1), "r"(a2), "r"(a3), "l"(b), "n"(ACC));
}
template <int ACC>
__device__ __forceinline__ void wg_rs32x(float* d, uint32_t a0, uint32_t a1, uint32_t a2, uint32_t a3, uint32_t blo) {
  asm volatile("{\n.reg .b64 b;\nmov.b64 b, {%20, 0x40000040};\n"
               "wgmma.mma_async.sync.aligned.m64n32k16.f32.bf16.bf16 {%0,%1,%2,%3,%4,%5,%6,%7,%8,%9,%10,%11,%12,%13,%14,%15}, {%16,%17,%18,%19}, b, %21, 1, 1, 0;\n}"
               : F16(d, 0) : "r"(a0), "r"(a1), "r"(a2), "r"(a3), "r"(blo), "n"(ACC));
}
template <int ACC>
__device__ __forceinline__ void wg_rs40(float* d, uint32_t a0, uint32_t a1, uint32_t a2, uint32_t a3, uint64_t b) {
  asm volatile("wgmma.mma_async.sync.aligned.m64n40k16.f32.bf16.bf16 {%0,%1,%2,%3,%4,%5,%6,%7,%8,%9,%10,%11,%12,%13,%14,%15,%16,%17,%18,%19}, {%20,%21,%22,%23}, %24, %25, 1, 1, 0;"
               : F16(d, 0), F4(d, 16) : "r"(a0), "r"(a1), "r"(a2), "r"(a3), "l"(b), "n"(ACC));
}
template <int ACC>
__device__ __forceinline__ void wg_ss8(float* d, uint64_t a, uint64_t b) {
  asm volatile("wgmma.mma_async.sync.aligned.m64n8k16.f32.bf16.bf16 {%0,%1,%2,%3}, %4, %5, %6, 1, 1, 0, 0;" : F4(d, 0) : "l"(a), "l"(b), "n"(ACC));
}
template <int ACC, int TA>
__device__ __forceinline__ void wg_ss40(float* d, uint64_t a, uint64_t b) {
  asm volatile("wgmma.mma_async.sync.aligned.m64n40k16.f32.bf16.bf16 {%0,%1,%2,%3,%4,%5,%6,%7,%8,%9,%10,%11,%12,%13,%14,%15,%16,%17,%18,%19}, %20, %21, %22, 1, 1, %23, 0;"
               : F16(d, 0), F4(d, 16) : "l"(a), "l"(b), "n"(ACC), "n"(TA));
}
template <int TA>
__device__ __forceinline__ void wg_ss128(float* d, uint64_t a, uint64_t b) {
  asm volatile("wgmma.mma_async.sync.aligned.m64n128k16.f32.bf16.bf16 {"
               "%0,%1,%2,%3,%4,%5,%6,%7,%8,%9,%10,%11,%12,%13,%14,%15,%16,%17,%18,%19,%20,%21,%22,%23,%24,%25,%26,%27,%28,%29,%30,%31,"
               "%32,%33,%34,%35,%36,%37,%38,%39,%40,%41,%42,%43,%44,%45,%46,%47,%48,%49,%50,%51,%52,%53,%54,%55,%56,%57,%58,%59,%60,%61,%62,%63"
               "}, %64, %65, 1, 1, 1, %66, 1;"
               : F16(d, 0), F16(d, 16), F16(d, 32), F16(d, 48) : "l"(a), "l"(b), "n"(TA));
}

__device__ __forceinline__ float bfr(float x) { return __bfloat162float(__float2bfloat16_rn(x)); }
constexpr int F_LN = 52, F_DONE = 53, F_W = 54, NHELP = 36;
__device__ __forceinline__ void ln_row(const uint2 (&u)[5], int row, int lane) {
  float v[20];
#pragma unroll
  for (int i = 0; i < 5; i++) {
    v[4 * i + 0] = __uint_as_float(u[i].x << 16); v[4 * i + 1] = __uint_as_float(u[i].x & 0xffff0000u);
    v[4 * i + 2] = __uint_as_float(u[i].y << 16); v[4 * i + 3] = __uint_as_float(u[i].y & 0xffff0000u);
  }
  float s = 0.f;
#pragma unroll
  for (int i = 0; i < 20; i++) s += v[i];
#pragma unroll
  for (int o = 16; o; o >>= 1) s += __shfl_xor_sync(~0u, s, o);
  const float mean = s * (1.0f / DM);
  float q = 0.f;
#pragma unroll
  for (int i = 0; i < 20; i++) { float d = v[i] - mean; q += d * d; }
#pragma unroll
  for (int o = 16; o; o >>= 1) q += __shfl_xor_sync(~0u, q, o);
  const float mb = bfr(mean), rs = 1.0f / bfr(sqrtf(bfr(bfr(q * (1.0f / DM)) + 1e-5f)));
  uint2* dst = reinterpret_cast<uint2*>(g_xn + (size_t)row * DM);
#pragma unroll
  for (int i = 0; i < 5; i++) {
    uint2 o;
    o.x = pack2(bfr(v[4 * i + 0] - mb) * rs, bfr(v[4 * i + 1] - mb) * rs);
    o.y = pack2(bfr(v[4 * i + 2] - mb) * rs, bfr(v[4 * i + 3] - mb) * rs);
    dst[i * 32 + lane] = o;
  }
}
__device__ __forceinline__ void wait_flag(const unsigned* f, unsigned target) {
  unsigned v; int n = 0;
  while (true) {
    asm volatile("ld.acquire.gpu.global.u32 %0, [%1];" : "=r"(v) : "l"(f) : "memory");
    if (v >= target) break;
    if (++n > (1 << 21)) __trap();
    __nanosleep(100);
  }
  asm volatile("fence.proxy.async.global;" ::: "memory");
}

namespace ck {
constexpr int CL = 6, NCL = 16, NRF = 8, NSS = 40 - NRF, NTP = 1;
constexpr uint32_t OFF_H = 0, OFF_WV = 51200, OFF_WO = OFF_WV + NSS * 2048, OFF_Q = OFF_WO + 86016, OFF_K = OFF_Q + 5120,
                   OFF_OG = OFF_K + 5120, OFF_RA = OFF_OG + 6144, OFF_P = OFF_RA + 3840, OFF_RT = OFF_P + 3200,
                   OFF_BAR = OFF_RT + 5120, SMEM = OFF_BAR + 256;
constexpr uint32_t B_X = 0, B_A = 8, B_T = 16, B_W = 24, B_WR = 32, B_B = 40  , B_XF = 88, B_DUMMY = 96, B_WO = 104,
                   B_ST = 128  ;
enum { NB_M = 1, NB_QK = 2, NB_PM = 3, NB_V = 4, NB_TS = 5, NB_P = 6, NB_G = 7, NB_R = 8  , NB_S = 12, NB_V2 = 13 };
static_assert(SMEM <= 232448, "smem");
static_assert(OFF_WO % 1024 == 0 && OFF_Q % 1024 == 0, "align");
}
__device__ __forceinline__ uint32_t opq(uint32_t x) { asm volatile("" : "+r"(x)); return x; }

__device__ __forceinline__ uint32_t memrow_addr(uint32_t sb, uint32_t col0, uint32_t m) {
  return sb + ck::OFF_H + (col0 >> 6) * 5120 + 4096 + m * 128 + ((((col0 >> 3) & 7) ^ m) << 4);
}
#define XPF 0
#define FLOODR 0
#define HWAIT 1
#define RSP 22
#define RSN 5
#define PFS 2
#define VLEAD 5
#define LW 24
#define EXP 0
template <int N> struct MemLoad { float4 c[N]; };
template <int N>
__device__ __forceinline__ void memload_issue(MemLoad<N>& m, int s, uint32_t warp, uint32_t lane) {
  const float4* p = g_acc + (s * ACC_CHUNKS + warp * 160) + lane;
#pragma unroll
  for (int q = 0; q < N; q++) m.c[q] = ld_relaxed4(p + q * 32);
}
template <int N>
__device__ __forceinline__ void memload_finish(MemLoad<N>& m, int s, uint32_t warp, uint32_t lane0, uint32_t sb, float full) {
  const uint32_t lane = opq(lane0);
  const uint32_t a4 = memrow_addr(sb, warp * 48 + (lane >> 3) * 8, lane & 7), a2 = memrow_addr(sb, warp * 48 + 32 + ((lane >> 3) & 1) * 8, lane & 7);
  const uint32_t a1 = memrow_addr(sb, 576 + warp * 8, lane & 7);
  int n = 0;
  while (true) {
    bool ok = true;
#pragma unroll
    for (int q = 0; q < N; q++) ok = ok && m.c[q].w == full;
    if (__all_sync(~0u, ok) || (EXP & 8)) break;
    if (++n > SPIN_LIMIT) __trap();
    memload_issue(m, s, warp, opq(lane0));
  }
  const float4* c = m.c;
  stsm4t(a4, pack2(c[0].x, c[1].x), pack2(c[2].x, c[3].x), pack2(c[0].y, c[1].y), pack2(c[2].y, c[3].y));
  stsm2t(a2, pack2(c[0].z, c[1].z), pack2(c[2].z, c[3].z));
  if (N == 5) stsm1t(a1, pack2(c[N - 1].x, c[N - 1].y + c[N - 1].z));
}
__device__ __forceinline__ uint32_t clk32() { uint32_t c; asm volatile("mov.u32 %0, %%clock;" : "=r"(c) :: "memory"); return c; }
#define WO_PREFETCH() _Pragma("unroll") for (int i = 0; i < 6; i++) \
  ldsm4t(f[i / 3][4 * (i % 3)], f[i / 3][4 * (i % 3) + 1], f[i / 3][4 * (i % 3) + 2], f[i / 3][4 * (i % 3) + 3], wo + (i % 3) * 12288 + (i / 3) * 2048)
#define HOFF(k) ((uint64_t)((((k) >> 2) * 5120 + ((k) & 3) * 32) >> 4))

template <bool LOADS>
__device__ __forceinline__ void token_qk(const uint32_t* a, int s, uint32_t sb, uint32_t warp, uint32_t lane0, uint32_t zero) {
  using namespace ck;
  const uint32_t bar = sb + OFF_BAR;
  float d[16];
  MemLoad<5> ml;
  mbar_wait(bar + B_X, (s + 1) & 1);
  if (LOADS && warp != 0) PROF(0, 4);
  const uint32_t db = opq((uint32_t)mkdesc(sb + OFF_H, 16, 1024, 1));
  WG_FENCE();
  wg_rs32x<0>(d, a[0], a[1], a[2], a[3], db);
#pragma unroll
  for (int k = 1; k < 40; k++) {
    wg_rs32x<1>(d, a[4 * k], a[4 * k + 1], a[4 * k + 2], a[4 * k + 3], db + (uint32_t)HOFF(k));
    if (LOADS && k == LW) WG_COMMIT();
  }
  WG_COMMIT();
  if (LOADS) { WG_WAIT(1); do { memload_issue(ml, s, warp, opq(lane0)); } while (zero >> 31); }
  WG_WAIT(0);
  const uint32_t e0 = pack2(d[0], d[1]);
  const uint32_t lane = opq(lane0), wg = warp >> 2, w4 = warp & 3;
  const uint32_t mat = lane >> 3, i = lane & 7, h = mat & 1, j0 = mat >> 1;
  const uint32_t ep0 = sb + OFF_Q + wg * 5120 + (8 * j0 + i) * 128 + (((2 * w4 + h) ^ i) << 4), ep1 = ep0 + 2048;
  if (LOADS) PROF(0, 5);
  stsm4t(ep0, e0, pack2(d[2], d[3]), pack2(d[4], d[5]), pack2(d[6], d[7]));
  stsm4t(ep1, pack2(d[8], d[9]), pack2(d[10], d[11]), pack2(d[12], d[13]), pack2(d[14], d[15]));
  if (LOADS) PROF(0, 6);
  const uint32_t dep = e0;
  if (LOADS) memload_finish(ml, s, warp, lane, sb, __uint_as_float(__float_as_uint((float)NCL) + (dep & zero)));
  if (LOADS) PROF(0, 7);
}

__global__ void __launch_bounds__(384, 1)
chain_kernel(const __grid_constant__ CUtensorMap tm_x, const __grid_constant__ CUtensorMap tm_wv, const __grid_constant__ CUtensorMap tm_wo,
             const __grid_constant__ CUtensorMap tm_wq, const __grid_constant__ CUtensorMap tm_wk, const bf16* __restrict__ mem0,
             const bf16* __restrict__ x, uint32_t zero) {
  using namespace ck;
  extern __shared__ __align__(1024) unsigned char smem[];
  const uint32_t sb = smem_u32(smem);
  const uint32_t tid0 = threadIdx.x;
  const uint32_t warp = __shfl_sync(~0u, threadIdx.x >> 5, 0);
  const int rank = blockIdx.x % CL, cluster = blockIdx.x / CL;
  const int hb = (rank / 3) * 3, j3 = rank % 3;
  const uint32_t bar = sb + OFF_BAR;

  asm volatile("griddepcontrol.launch_dependents;");
  const int gw = (tid0 >> 5) * 96 + blockIdx.x;
  uint2 xu[2][5];
  uint4 m0u[5];
#pragma unroll
  for (int r = 0; r < 5; r++) m0u[r] = __ldg(reinterpret_cast<const uint4*>(mem0) + (tid0 & 127) + r * 128);
#pragma unroll
  for (int r = 0; r < 2; r++) {
    const int row = min(gw + r * 1152, SEQ - 1);
#pragma unroll
    for (int j = 0; j < 5; j++) xu[r][j] = __ldg(reinterpret_cast<const uint2*>(x + (size_t)row * DM) + j * 32 + (tid0 & 31));
  }
  if (tid0 == 0) {
    mbar_init(bar + B_X, 1); mbar_init(bar + B_A, 1); mbar_init(bar + B_T, 1); mbar_init(bar + B_W, 1); mbar_init(bar + B_WR, 1);
    for (int i = 0; i < 3; i++) mbar_init(bar + B_B + 8 * i, 1);
    for (int i = 0; i < 10; i++) mbar_init(bar + B_ST + 8 * i, 1);
    mbar_init(bar + B_XF, 1); mbar_init(bar + B_WO, 1);
    asm volatile("fence.mbarrier_init.release.cluster;" ::: "memory");
    mbar_expect(bar + B_A, 3 * 1024); mbar_expect(bar + B_T, 2 * 2560);
    for (int i = 0; i < 3; i++) mbar_expect(bar + B_B + 8 * i, 2048);
    for (int i = 0; i < 10; i++) mbar_expect(bar + B_ST + 8 * i, 16384);
    mbar_expect(bar + B_XF, CL * 4);
    mbar_expect(bar + B_X, 40960);
    mbar_expect(bar + B_WR, NRF * 2048);
    mbar_expect(bar + B_W, NSS * 2048); mbar_expect(bar + B_WO, (rank < 4 ? 7 : 6) * 12288);
    tma2d(sb + OFF_H, &tm_wv, blockIdx.x * 64, NSS * 16, bar + B_WR);
  }
  {
    const float4 z = make_float4(0.f, 0.f, 0.f, 0.f);
    for (int j = blockIdx.x * 384 + tid0; j < NSEG * ACC_CHUNKS; j += 96 * 384) g_acc[j] = z;
    for (int j = blockIdx.x * 384 + tid0; j < 20 * 4096; j += 96 * 384) g_part[j] = z;
  }
#pragma unroll 1
  for (int r = 0; r < 2; r++) {
    if (gw + r * 1152 < SEQ) ln_row(xu[0], gw + r * 1152, tid0 & 31);
#pragma unroll
    for (int j = 0; j < 5; j++) xu[0][j] = xu[1][j];
    if (r == FLOODR && tid0 < 10) {
      const uint32_t wg = tid0 & 1, i = tid0 >> 1;
      tma2d(sb + (wg == 0 ? OFF_WO + i * 16384 : i < 4 ? OFF_WV + i * 16384 : OFF_Q), wg == 0 ? &tm_wq : &tm_wk, blockIdx.x * 64, i * 128,
            bar + B_ST + 8 * (wg * 5 + i));
    }
    __syncwarp();
  }
  __threadfence();
  __syncthreads();
  PPROF(320, 0);
  if (tid0 == 320) atomicAdd(&g_flag[F_LN], 1u);
  PPROF(320, 1);
  asm volatile("barrier.cluster.arrive.relaxed.aligned;" ::: "memory");

  if (warp < 8) {
    asm volatile("setmaxnreg.inc.sync.aligned.u32 208;");
    const uint32_t lane0 = __shfl_sync(~0u, opq(threadIdx.x & 31), threadIdx.x & 31);
    uint32_t a[160];
    {
      const uint32_t wg = warp >> 2, l7 = lane0 & 7, l3 = lane0 >> 3, t128 = tid0 & 127;
      const uint32_t lo = ((l3 >> 1) * 8 + l7) * 128 + (((2 * (warp & 3) + (l3 & 1)) ^ l7) << 4);
#pragma unroll
      for (int i = 0; i < 5; i++) {
        const uint32_t base = sb + (wg == 0 ? OFF_WO + i * 16384 : i < 4 ? OFF_WV + i * 16384 : OFF_Q) + lo;
        mbar_wait(bar + B_ST + 8 * (wg * 5 + i), 0);
#pragma unroll
        for (int k = 0; k < 8; k++) ldsm4t(a[32 * i + 4 * k], a[32 * i + 4 * k + 1], a[32 * i + 4 * k + 2], a[32 * i + 4 * k + 3], base + k * 2048);
        asm volatile("" :: "r"(a[32 * i]), "r"(a[32 * i + 4]), "r"(a[32 * i + 8]), "r"(a[32 * i + 12]), "r"(a[32 * i + 16]), "r"(a[32 * i + 20]), "r"(a[32 * i + 24]), "r"(a[32 * i + 28]) : "memory");
        bar_sync(NB_R + wg, 128);
        if (wg == 1) {
          if (t128 == 0 && i < 4) tma2d(sb + OFF_WV + i * 16384, &tm_wv, blockIdx.x * 64, i * 128, bar + B_W);
        } else {
          const int t0 = (4 * i) / 3, t1 = i == 4 ? (rank < 4 ? 7 : 6) : (4 * i + 4) / 3;
          const int t = t0 + t128 / 6, d = t128 % 6;
          if (t < t1) tma2d(sb + OFF_WO + t * 12288 + d * 2048, &tm_wo, t < 6 ? rank * 96 + t * 16 : 576 + rank * 16,
                            cluster * 384 + ((rank + CL - d) % CL) * 64, bar + B_WO);
        }
        __syncwarp();
      }
      bar_sync(NB_QK, 256);
    }
    PPROF(0, 2);
    token_qk<false>(a, -1, sb, warp, lane0, zero);
    PPROF(0, 3);
    asm volatile("barrier.cluster.wait.acquire.aligned;" ::: "memory");
    const float sc = 0.07216878364870322f * 1.4426950408889634f;

    for (int s = 0;; s++) {
      uint32_t lane;
      {
        const uint32_t ln = opq(lane0);
        const uint32_t x0 = sb + OFF_H + 4096 + (ln & 7) * 128 + (((ln >> 3) ^ (ln & 7)) << 4), x1 = x0 ^ 64;
        float c[16];
#pragma unroll
        for (int i = 0; i < 16; i++) c[i] = 0.f;
        uint32_t bf[1][16];
        bar_sync(NB_M, 384);
        PROF(0, 0);
#pragma unroll
        for (int k = 0; k < 40; k += 2) {
          uint32_t* b = bf[0] + 12;
          ldsm4(b[0], b[1], b[2], b[3], ((k & 2) ? x1 : x0) + (k >> 2) * 5120);
          float* d = c + ((k & 2) ? 8 : 0);
          mma16816(d, a[4 * k], a[4 * k + 1], a[4 * k + 2], a[4 * k + 3], b[0], b[1]);
          mma16816(d + 4, a[4 * k + 4], a[4 * k + 5], a[4 * k + 6], a[4 * k + 7], b[2], b[3]);
        }
#pragma unroll
        for (int i = 0; i < 4; i++) c[i] = (c[i] + c[4 + i]) + (c[8 + i] + c[12 + i]);
        asm volatile("add.u32 %0, %1, %2;" : "=r"(lane) : "r"(lane0), "r"(bf[0][15] & zero));
        const uint32_t qst = sb + OFF_Q + (warp >> 2) * 5120 + (32 + (lane & 7)) * 128 + (((2 * (warp & 3) + ((lane >> 3) & 1)) ^ (lane & 7)) << 4);
        stsm2t(qst, pack2(c[0], c[1]), pack2(c[2], c[3]));
        PROF(0, 1);
      }
      const uint32_t l7 = lane & 7, l3 = lane >> 3;
      fence_async();
      bar_arrive(NB_S, 384);
      SPROF();
      if (s == NSEG - 1) break;
      if (s == 0) { mbar_wait(bar + B_WO, 0); PPROF(0, 4); if (tid0 == 64) atomicAdd(&g_flag[F_W], 1u); }
      const uint32_t grp = warp >> 2, kq = warp & 3;
      const uint32_t wo = sb + OFF_WO + grp * 36864 + kq * 512 + ((l3 >> 1) * 8 + l7) * 32 + (((l3 & 1) ^ (kq >> 1) ^ (l7 >> 2)) << 4);
      uint32_t f[2][12];
      if (warp == 0) {
        const uint32_t ra = sb + OFF_RA + lane * 16;
        mbar_wait(bar + B_A, s & 1);
        PROF(0, 3);
        uint32_t t[15];
#pragma unroll
        for (int j = 0; j < 3; j++) ldsm4t(t[4 * j], t[4 * j + 1], t[4 * j + 2], t[4 * j + 3], ra + j * 1024);
        { uint32_t unused; ldsm4t(t[12], t[13], t[14], unused, sb + OFF_RA + 512 + (l3 == 3 ? 0 : l3) * 1024 + l7 * 16); }
        float p[10];
#pragma unroll
        for (int i = 0; i < 5; i++) {
          const uint32_t x = i < 4 ? t[i] : t[12], y = i < 4 ? t[4 + i] : t[13], z = i < 4 ? t[8 + i] : t[14];
          p[2 * i] = (__uint_as_float(x << 16) + __uint_as_float(y << 16)) + __uint_as_float(z << 16);
          p[2 * i + 1] = (__uint_as_float(x & 0xffff0000u) + __uint_as_float(y & 0xffff0000u)) + __uint_as_float(z & 0xffff0000u);
        }
        float mx = fmaxf(fmaxf(fmaxf(p[0], p[1]), fmaxf(p[2], p[3])), fmaxf(fmaxf(p[4], p[5]), fmaxf(p[6], p[7])));
        mx = fmaxf(mx, fmaxf(p[8], p[9]));
        mx = fmaxf(mx, __shfl_xor_sync(~0u, mx, 1)); mx = fmaxf(mx, __shfl_xor_sync(~0u, mx, 2));
#pragma unroll
        for (int i = 0; i < 10; i++) p[i] = ex2(fmaf(p[i], sc, -mx * sc));
        sts4u(sb + OFF_P + lane * 16, make_uint4(pack2(p[0], p[1]), pack2(p[2], p[3]), pack2(p[4], p[5]), pack2(p[6], p[7])));
        sts1u(sb + OFF_P + 512 + lane * 4, pack2(p[8], p[9]));
        bar_arrive(NB_PM, 160);
        if (lane == 0) mbar_expect(bar + B_A, 3 * 1024);
        PROF(0, 4);
      } else {
        const uint32_t rb = mapa(sb, lane < CL ? lane : 0);
        bar_sync(NB_V2, 352);
        if (warp == 1 && lane < CL) st_async1(rb + OFF_BAR + B_DUMMY, 0u, rb + OFF_BAR + B_XF);
        if (warp == 2) {
          if (lane == 0) mbar_expect(bar + B_X, 40960);
          mbar_wait(bar + B_XF, s & 1);
          if (lane == 0) mbar_expect(bar + B_XF, CL * 4);
          const int c2 = rank + 6 * lane;
          if (c2 < 10) {
            tma2d_mc(sb + OFF_H + c2 * 5120, &tm_x, c2 * 64, (s + 1) * 32, bar + B_X, (uint16_t)0x3f);
          }
          __syncwarp();
        }
      }
      {
        const uint32_t og = sb + OFF_OG + kq * 256 + (lane ^ ((kq & 1) << 2)) * 8;
        float v[12];
#pragma unroll
        for (int i = 0; i < 12; i++) v[i] = 0.f;
        bar_sync(NB_V, 384);
        WO_PREFETCH();
        bar_sync(NB_TS, 384);
#pragma unroll
        for (int u = 0; u < 3; u++) {
          mbar_wait(bar + B_B + 8 * u, s & 1);
          if (u == 0) PROF(0, 2);
          const float2 o0 = lds2f(og + u * 2048), o1 = lds2f(og + u * 2048 + 1024);
#pragma unroll
          for (int h = 0; h < 2; h++) {
            uint32_t* ff = f[h];
#pragma unroll
            for (int i = 0; i < 3; i++)
              mma16816(v + 4 * i, ff[4 * i], ff[4 * i + 1], ff[4 * i + 2], ff[4 * i + 3], __float_as_uint(h ? o1.x : o0.x), __float_as_uint(h ? o1.y : o0.y));
            if (u < 2) {
#pragma unroll
              for (int i = 0; i < 3; i++) ldsm4t(ff[4 * i], ff[4 * i + 1], ff[4 * i + 2], ff[4 * i + 3], wo + (2 * u + 2 + h) * 2048 + i * 12288);
            }
          }
        }
        const uint32_t xb = sb + OFF_Q + grp * 4608;
#pragma unroll
        for (int i = 1; i < 4; i++) {
          const uint32_t x = xb + ((i ^ kq) * 3 + (i - 1)) * 384;
          sts2f(x + lane * 8, v[i], v[4 + i]); sts1f(x + 256 + lane * 4, v[8 + i]);
        }
        float4* o = g_acc + (s * ACC_CHUNKS + (2 * rank + grp) * 160 + kq * 32) + lane;
        const uint32_t y = xb + kq * 1152;
        bar_sync(NB_R + grp, 128);
        const float2 p0 = lds2f(y + lane * 8), p1 = lds2f(y + 384 + lane * 8), p2 = lds2f(y + 768 + lane * 8);
        const float q0 = lds1f(y + 256 + lane * 4), q1 = lds1f(y + 640 + lane * 4), q2 = lds1f(y + 1024 + lane * 4);
        red4(o, (v[0] + p0.x) + (p1.x + p2.x), (v[4] + p0.y) + (p1.y + p2.y), (v[8] + q0) + (q1 + q2), 1.0f);
        if (warp) PROF(0, 3);
      }
      bar_sync(NB_G, 384);
      token_qk<true>(a, s, sb, warp, lane0, zero);
    }
    cluster_sync();
  } else {
    asm volatile("setmaxnreg.dec.sync.aligned.u32 88;");
    const uint32_t lane0 = __shfl_xor_sync(~0u, opq((threadIdx.x & 31) ^ 1), 1);
    uint32_t wv[4 * NRF];
    {
      const int i = tid0 - 256;
      mbar_wait(bar + B_WR, 0);
      const uint32_t l7 = lane0 & 7, l3 = lane0 >> 3;
#pragma unroll
      for (int k = 0; k < NRF; k++)
        ldsm4t(wv[4 * k], wv[4 * k + 1], wv[4 * k + 2], wv[4 * k + 3], sb + OFF_H + k * 2048 + ((l3 >> 1) * 8 + l7) * 128 + (((2 * (warp - 8) + (l3 & 1)) ^ l7) << 4));
      asm volatile("" :: "r"(wv[0]), "r"(wv[4]), "r"(wv[8]), "r"(wv[12]), "r"(wv[16]), "r"(wv[20]), "r"(wv[24]), "r"(wv[28]) : "memory");
      bar_sync(NB_P, 128);
#pragma unroll
      for (int r = 0; r < 5; r++) { const uint32_t j = i + r * 128; sts4u(memrow_addr(sb, (j % 80) * 8, j / 80), m0u[r]); }
      fence_async();
      if (i == 96) {
        wait_flag(&g_flag[F_LN], 96);
        PPROF(352, 5);
        for (int c = 0; c < 10; c++) tma2d(sb + OFF_H + c * 5120, &tm_x, c * 64, 0, bar + B_X);
      }
      __syncwarp();
    }
    PPROF(256, 6);
    mbar_wait(bar + B_W, 0);
    PPROF(256, 7);
    asm volatile("barrier.cluster.wait.acquire.aligned;" ::: "memory");
    const float sc = 0.07216878364870322f * 1.4426950408889634f;

    bar_arrive(NB_M, 384);
    for (int s = 0; s < NSEG; s++) {
      const bool last = s == NSEG - 1;
      uint32_t va[10];
      {
        uint32_t wt_[4 * NTP];
        {
          const uint32_t ln = opq(lane0), l7 = ln & 7, l3 = ln >> 3;
#pragma unroll
          for (int k = 0; k < NTP; k++)
            ldsm4t(wt_[4 * k], wt_[4 * k + 1], wt_[4 * k + 2], wt_[4 * k + 3],
                   sb + OFF_WV + (NSS - NTP + k) * 2048 + ((l3 >> 1) * 8 + l7) * 128 + (((2 * (warp - 8) + (l3 & 1)) ^ l7) << 4));
        }
        mbar_wait(bar + B_X, s & 1);
        float v[20];
        uint64_t db = mkdesc(sb + OFF_H, 16, 1024, 1), da = mkdesc(sb + OFF_WV, 1024, 1024, 1);
        OPAQUE64(db); OPAQUE64(da);
        uint64_t dk = mkdesc(sb + OFF_K, 16, 1024, 1), dq = mkdesc(sb + OFF_Q + 4096, 16, 1024, 1);
        OPAQUE64(dk); OPAQUE64(dq);
        const uint32_t ra = OFF_RA + j3 * 1024 + (warp - 8) * 256 + opq(lane0) * 4;
        float sm[4];
        PROF(2, 0);
        bar_sync(NB_S, 384);
        WG_FENCE();
        wg_ss8<0>(sm, dk, dq); wg_ss8<1>(sm, dk + 2, dq + 2); wg_ss8<1>(sm, dk + 4, dq + 4); wg_ss8<1>(sm, dk + 6, dq + 6);
        WG_COMMIT();
        wg_ss40<0, 1>(v, da, db);
#pragma unroll
        for (int k = 1; k < VLEAD; k++) wg_ss40<1, 1>(v, da + (uint64_t)(k * 128), db + HOFF(k));
        WG_COMMIT();
        WG_WAIT(1);
        {
          const uint32_t x = pack2(sm[0], sm[1]), y = pack2(sm[2], sm[3]);
#pragma unroll
          for (int d = 0; d < 3; d++) {
            const uint32_t rb = mapa(sb, hb + (j3 + 1 + d) % 3);
            st_async1(rb + ra, x, rb + OFF_BAR + B_A); st_async1(rb + ra + 128, y, rb + OFF_BAR + B_A);
          }
        }
#pragma unroll
        for (int k = VLEAD; k < RSP; k++) wg_ss40<1, 1>(v, da + (uint64_t)(k * 128), db + HOFF(k));
#pragma unroll
        for (int k = NSS; k < NSS + RSN; k++) wg_rs40<1>(v, wv[4 * (k - NSS)], wv[4 * (k - NSS) + 1], wv[4 * (k - NSS) + 2], wv[4 * (k - NSS) + 3], db + HOFF(k));
#pragma unroll
        for (int k = RSP; k < NSS - NTP; k++) wg_ss40<1, 1>(v, da + (uint64_t)(k * 128), db + HOFF(k));
#pragma unroll
        for (int k = 0; k < NTP; k++) wg_rs40<1>(v, wt_[4 * k], wt_[4 * k + 1], wt_[4 * k + 2], wt_[4 * k + 3], db + HOFF(NSS - NTP + k));
#pragma unroll
        for (int k = NSS + RSN; k < 40; k++) wg_rs40<1>(v, wv[4 * (k - NSS)], wv[4 * (k - NSS) + 1], wv[4 * (k - NSS) + 2], wv[4 * (k - NSS) + 3], db + HOFF(k));
        WG_COMMIT();
        WG_WAIT(0);
#pragma unroll
        for (int i = 0; i < 10; i++) va[i] = pack2(v[2 * i], v[2 * i + 1]);
      }
      PROF(2, 1);
      const uint32_t lane = opq(lane0), w4 = warp - 8, wt = w4 * 32 + lane;
      if (!last) {
        bar_arrive(NB_V2, 352);
        uint32_t da_[CL], db_[CL];
#pragma unroll
        for (int d = 0; d < CL; d++) {
          int r = rank + d; if (r >= CL) r -= CL;
          const uint32_t rb = mapa(sb, r);
          da_[d] = opq(rb + OFF_OG + wt * 8 + d * 1024); db_[d] = opq(rb + OFF_BAR + B_B + 8 * (d >> 1));
        }
        bar_sync(NB_PM, 160);
        const uint4 pa = lds4u(sb + OFF_P + lane * 16);
        const uint32_t pb = __float_as_uint(lds1f(sb + OFF_P + 512 + lane * 4));
        float o0[4] = {0.f, 0.f, 0.f, 0.f}, o1[4] = {0.f, 0.f, 0.f, 0.f}, o2[4] = {0.f, 0.f, 0.f, 0.f}, o3[4] = {0.f, 0.f, 0.f, 0.f};
        float os[4] = {0.f, 0.f, 0.f, 0.f};
        mma16816(os, pa.x, pa.z, pa.y, pa.w, 0x3f803f80u, 0x3f803f80u);
        mma16816(o0, pa.x, 0u, pa.y, 0u, va[0], va[2]);
        mma16816(o1, pa.x, 0u, pa.y, 0u, va[1], va[3]);
        mma16816(o2, pa.z, 0u, pa.w, 0u, va[4], va[6]);
        mma16816(os, pb, 0u, 0u, 0u, 0x3f803f80u, 0u);
        mma16816(o3, pa.z, 0u, pa.w, 0u, va[5], va[7]);
        mma16816(o0, pb, 0u, 0u, 0u, va[8], 0u);
        mma16816(o1, pb, 0u, 0u, 0u, va[9], 0u);
        const float inv = rcp(os[0] + os[2]);
        const uint32_t x = pack2((o0[0] + o2[0]) * inv, (o0[1] + o2[1]) * inv), y = pack2((o1[0] + o3[0]) * inv, (o1[1] + o3[1]) * inv);
#pragma unroll
        for (int d = 0; d < CL; d++) st_async2(da_[d], x, y, db_[d]);
        bar_arrive(NB_V, 384);
        PROF(2, 3);
      }
      uint32_t e[5];
      {
        float v[20];
        uint64_t da = mkdesc(sb + OFF_Q, 16, 512, 1), db = mkdesc(sb + OFF_K, 16, 1024, 1);
        OPAQUE64(db); OPAQUE64(da);
        WG_FENCE();
        wg_ss40<0, 0>(v, da, db);
        wg_ss40<1, 0>(v, da + 2, db + 2);
        wg_ss40<1, 0>(v, da + 4, db + 4);
        wg_ss40<1, 0>(v, da + 6, db + 6);
        WG_COMMIT();
        WG_WAIT(0);
#pragma unroll
        for (int i = 0; i < 5; i++) e[i] = pack2(v[4 * i], v[4 * i + 1]);
      }
      if (!last) {
        bar_arrive(NB_TS, 384);
        if (w4 == 0) {
        } else if (w4 == 3) {
          if ((s & 3) == 0 && s > 0 && lane == 0) { __threadfence(); atomicAdd(&g_flag[(s >> 2) - 1], 1u); }
          __syncwarp();
        } else if (rank < 4) {
          if (s == 0) mbar_wait(bar + B_WO, 0);
          const uint32_t kh = w4 - 1, l7 = lane & 7, l3 = lane >> 3;
          const uint32_t wo = sb + OFF_WO + 6 * 12288 + kh * 2048 + ((l3 >> 1) * 8 + l7) * 32 + (((l3 & 1) ^ (l7 >> 2)) << 4);
          const uint32_t og = sb + OFF_OG + kh * 1024 + lane * 8;
          float u[4] = {0.f, 0.f, 0.f, 0.f};
#pragma unroll
          for (int it = 0; it < 3; it++) {
            uint32_t ff[16];
#pragma unroll
            for (int kk = 0; kk < 4; kk++) ldsm4t(ff[4 * kk], ff[4 * kk + 1], ff[4 * kk + 2], ff[4 * kk + 3], wo + it * 4096 + kk * 512);
            mbar_wait(bar + B_B + 8 * it, s & 1);
#pragma unroll
            for (int kk = 0; kk < 4; kk++) {
              const float2 o = lds2f(og + it * 2048 + kk * 256);
              mma16816(u, ff[4 * kk], ff[4 * kk + 1], ff[4 * kk + 2], ff[4 * kk + 3], __float_as_uint(o.x), __float_as_uint(o.y));
            }
          }
          const uint32_t xb = sb + OFF_RA + lane * 8;
          sts2f(xb + kh * 256, kh ? u[0] : u[2], kh ? u[1] : u[3]);
          float4* o = g_acc + (s * ACC_CHUNKS + (2 * rank + kh) * 160 + 128) + lane;
          bar_sync(NB_R + 2, 64);
          const float2 x = lds2f(xb + 256 - kh * 256);
          red4(o, (kh ? u[2] : u[0]) + x.x, (kh ? u[3] : u[1]) + x.y, 0.f, 1.0f);
        }
        bar_sync(NB_G, 384);
        if (wt < 3) mbar_expect(bar + B_B + 8 * wt, 2048);
      }
      {
#pragma unroll
        for (int d = 1; d <= 2; d++) {
          const uint32_t rb = mapa(sb, hb + (j3 + d) % 3);
          st_async4(rb + OFF_RT + (2 - d) * 2560 + wt * 16, e[0], e[1], e[2], e[3], rb + OFF_BAR + B_T);
          st_async1(rb + OFF_RT + (2 - d) * 2560 + 2048 + wt * 4, e[4], rb + OFF_BAR + B_T);
        }
      }
      PROF(2, 4);
      mbar_wait(bar + B_T, s & 1);
      PROF(2, 5);
      float p[10];
#pragma unroll
      for (int i = 0; i < 5; i++) { p[2 * i] = __uint_as_float(e[i] << 16); p[2 * i + 1] = __uint_as_float(e[i] & 0xffff0000u); }
#pragma unroll
      for (int d = 0; d < 2; d++) {
        const uint4 x = lds4u(sb + OFF_RT + d * 2560 + wt * 16);
        const uint32_t y = __float_as_uint(lds1f(sb + OFF_RT + d * 2560 + 2048 + wt * 4));
        p[0] += __uint_as_float(x.x << 16); p[1] += __uint_as_float(x.x & 0xffff0000u);
        p[2] += __uint_as_float(x.y << 16); p[3] += __uint_as_float(x.y & 0xffff0000u);
        p[4] += __uint_as_float(x.z << 16); p[5] += __uint_as_float(x.z & 0xffff0000u);
        p[6] += __uint_as_float(x.w << 16); p[7] += __uint_as_float(x.w & 0xffff0000u);
        p[8] += __uint_as_float(y << 16); p[9] += __uint_as_float(y & 0xffff0000u);
      }
      if (wt == 0) mbar_expect(bar + B_T, 2 * 2560);
      MemLoad<4> ml;
      do { memload_issue(ml, last ? 0 : s, warp, lane); } while (zero >> 31);
      PROF(2, 2);
      {
        const int tq = 8 * w4 + (lane >> 2) - 2 * (lane & 3);
        float mx = fmaxf(p[8], p[9]);
#pragma unroll
        for (int i = 0; i < 8; i++) { if (8 * (i >> 1) + (i & 1) > tq) p[i] = -INFINITY; mx = fmaxf(mx, p[i]); }
        mx = fmaxf(mx, __shfl_xor_sync(~0u, mx, 1)); mx = fmaxf(mx, __shfl_xor_sync(~0u, mx, 2));
        float sum = 0.f;
#pragma unroll
        for (int i = 0; i < 10; i++) { p[i] = ex2(fmaf(p[i], sc, -mx * sc)); sum += p[i]; }
        sum += __shfl_xor_sync(~0u, sum, 1); sum += __shfl_xor_sync(~0u, sum, 2);
        const float inv = rcp(sum);
        const uint32_t pr = sb + OFF_P + (lane >> 3) * 800 + w4 * 32 + (lane & 7) * 4;
#pragma unroll
        for (int i = 0; i < 5; i++) sts1u(pr + i * 128, pack2(p[2 * i] * inv, p[2 * i + 1] * inv));
        sts1u(pr + 640, 0u);
      }
      if (!last) {
        memload_finish(ml, s, warp, lane, sb, (float)NCL);
        bar_arrive(NB_M, 384);
      }
      fence_async();
      PROF(2, 7);
      bar_sync(NB_P, 128);
      {
        float o[16];
        uint64_t db = mkdesc(sb + OFF_P, 128, 800, 0);
        OPAQUE64(db);
        uint32_t vb[10];
#pragma unroll
        for (int i = 0; i < 10; i++) asm volatile("add.u32 %0, %1, %2;" : "=r"(vb[i]) : "r"(va[i]), "r"(zero));
        WG_FENCE();
        wg_rs32<0>(o, vb[0], vb[1], vb[2], vb[3], db);
        wg_rs32<1>(o, vb[4], vb[5], vb[6], vb[7], db + 16);
        wg_rs32<1>(o, vb[8], vb[9], 0u, 0u, db + 32);
        WG_COMMIT();
        uint4* dst = reinterpret_cast<uint4*>(g_oT) + ((s * HD + blockIdx.x * 64 + w4 * 16) * 4 + lane);
        WG_WAIT(0);
        dst[0] = make_uint4(pack2(o[0], o[1]), pack2(o[4], o[5]), pack2(o[8], o[9]), pack2(o[12], o[13]));
        dst[32] = make_uint4(pack2(o[2], o[3]), pack2(o[6], o[7]), pack2(o[10], o[11]), pack2(o[14], o[15]));
      }
      PROF(2, 6);
    }
    bar_sync(NB_P, 128);
    if (tid0 == 256) { __threadfence(); atomicAdd(&g_flag[15], 1u); }
    cluster_sync();
  }
}

namespace hk {
constexpr int STAGES = 4, STAGE = 49152, OFF_ST = STAGES * STAGE, OFF_BAR = OFF_ST + 32768, SMEM = OFF_BAR + 1024, NCTA = NHELP;
constexpr int N_G1 = 192, SB0 = 12  , N_FULL = 5 * SB0, N_ITEMS = N_G1 + 20 + N_FULL + 5 * (2 + 4 + 7) + 1 + 35;
struct Item { int type, mb, nt, k0, k1, nsplit; };
__device__ __forceinline__ Item get_item(int i) {
  Item t;
  if (i < N_G1) { t.type = 0; t.mb = i / 12; t.nt = i % 12; t.k0 = 0; t.k1 = 10; t.nsplit = 1; return t; }
  i -= N_G1; t.type = 1; t.nt = i % 5;
  if (i < 20) { t.mb = SB0 + i / 5; t.k0 = 0; t.k1 = 24; t.nsplit = t.mb == 12 ? 3 : t.mb == 13 ? 5 : 8; return t; }
  i -= 20;
  if (i < N_FULL) { t.mb = i / 5; t.k0 = 0; t.k1 = 120; t.nsplit = 1; return t; }
  i -= N_FULL;
  int ns;
  if (i < 10) { t.mb = 12; ns = 2; } else if (i < 30) { i -= 10; t.mb = 13; ns = 4; } else if (i < 65) { i -= 30; t.mb = 14; ns = 7; }
  else if (i == 65) { t.type = 2; t.mb = t.k0 = t.k1 = 0; t.nsplit = 1; return t; }
  else { i -= 66; t.mb = 15; ns = 7; }
  t.nt = i % 5;
  const int p = i / 5;
  t.k0 = 24 + (96 * p) / ns; t.k1 = 24 + (96 * (p + 1)) / ns; t.nsplit = ns + 1;
  return t;
}
__device__ __forceinline__ void store_tile(const uint32_t* p, uint32_t stg, const CUtensorMap* tm, int c0, int r0, int wg, int t128) {
  const int lane = t128 & 31, r = (t128 >> 5) * 16 + (lane & 15);
  if (t128 == 0) asm volatile("cp.async.bulk.wait_group.read 0;" ::: "memory");
  bar_sync(1 + wg, 128);
#pragma unroll
  for (int j = 0; j < 8; j++) {
    const int c = 2 * j + (lane >> 4);
    const uint32_t a = stg + (c >> 3) * 8192 + r * 128 + (((c & 7) ^ (r & 7)) << 4);
    asm volatile("stmatrix.sync.aligned.m8n8.x4.shared.b16 [%0], {%1,%2,%3,%4};" :: "r"(a), "r"(p[4 * j]), "r"(p[4 * j + 1]), "r"(p[4 * j + 2]), "r"(p[4 * j + 3]) : "memory");
  }
  fence_async();
  bar_sync(1 + wg, 128);
  if (t128 == 0) {
    asm volatile("cp.async.bulk.tensor.2d.global.shared::cta.bulk_group [%0, {%2, %3}], [%1];" :: "l"(tm), "r"(stg), "r"(c0), "r"(r0) : "memory");
    asm volatile("cp.async.bulk.tensor.2d.global.shared::cta.bulk_group [%0, {%2, %3}], [%1];" :: "l"(tm), "r"(stg + 8192), "r"(c0 + 64), "r"(r0) : "memory");
    asm volatile("cp.async.bulk.commit_group;" ::: "memory");
  }
}
}
__global__ void __launch_bounds__(384, 1)
helper_kernel(const __grid_constant__ CUtensorMap tm_x, const __grid_constant__ CUtensorMap tm_g, const __grid_constant__ CUtensorMap tm_u,
              const __grid_constant__ CUtensorMap tm_h, const __grid_constant__ CUtensorMap tm_o, const __grid_constant__ CUtensorMap tm_wd,
              const __grid_constant__ CUtensorMap tm_wo, const __grid_constant__ CUtensorMap tm_hs, const __grid_constant__ CUtensorMap tm_out,
              const bf16* __restrict__ x) {
  using namespace hk;
  extern __shared__ __align__(1024) unsigned char smem[];
  const uint32_t sb = smem_u32(smem), bar = sb + OFF_BAR;
  const int tid = threadIdx.x, lane = tid & 31, wg = __shfl_sync(~0u, tid >> 7, 0);
  if (tid == 0) { for (int i = 0; i < STAGES; i++) { mbar_init(bar + 8 * i, 1); mbar_init(bar + 64 + 8 * i, 2); } asm volatile("fence.mbarrier_init.release.cluster;" ::: "memory"); }
  __syncthreads();
  const int i0 = blockIdx.x;
  if (wg == 2) {
    asm volatile("setmaxnreg.dec.sync.aligned.u32 40;");
    if (tid == 256) {
      uint32_t it = 0;
      wait_flag(&g_flag[F_LN], 96);
      if (HWAIT) wait_flag(&g_flag[F_W], 48);
      for (int i = i0; i < N_ITEMS; i += NCTA) {
        const Item t = get_item(i);
        const int m0 = t.mb * 128, n0 = t.nt * 128;
        int kb = t.k0;
        if (t.type == 1 && kb == 0) wait_flag(&g_flag[16 + t.mb], 24);
        for (; kb < t.k1 && kb < 24; kb++, it++) {
          const uint32_t st = it % STAGES, base = sb + st * STAGE, full = bar + 8 * st;
          mbar_wait_long(bar + 64 + 8 * st, ((it / STAGES) & 1) ^ 1);
          if (t.type == 0) {
            mbar_expect(full, 49152);
            tma2d(base, &tm_x, kb * 64, m0, full);
            tma2d(base + 16384, &tm_g, n0, kb * 64, full);
            tma2d(base + 24576, &tm_g, n0 + 64, kb * 64, full);
            tma2d(base + 32768, &tm_u, n0, kb * 64, full);
            tma2d(base + 40960, &tm_u, n0 + 64, kb * 64, full);
          } else {
            mbar_expect(full, 32768);
            tma2d(base, &tm_h, kb * 64, m0, full);
            tma2d(base + 16384, &tm_wd, n0, kb * 64, full);
            tma2d(base + 24576, &tm_wd, n0 + 64, kb * 64, full);
          }
        }
        const int kf = kb;
        for (; kb < t.k1; kb++, it++) {
          const uint32_t st = it % STAGES, base = sb + st * STAGE, full = bar + 8 * st;
          const int k0 = (kb - 24) * 64;
          mbar_wait_long(bar + 64 + 8 * st, ((it / STAGES) & 1) ^ 1);
          mbar_expect(full, 32768);
          tma2d(base + 16384, &tm_wo, n0, k0, full);
          tma2d(base + 24576, &tm_wo, n0 + 64, k0, full);
          if (kb == kf + STAGES - 2) {
            wait_flag(&g_flag[t.mb], 96);
            for (int j = STAGES - 2; j > 0; j--) tma3d(sb + ((it - j) % STAGES) * STAGE, &tm_o, 0, k0 - j * 64, m0 / 32, bar + 8 * ((it - j) % STAGES));
          }
          if (kb >= kf + STAGES - 2) tma3d(base, &tm_o, 0, k0, m0 / 32, full);
        }
      }
    }
  } else {
    asm volatile("setmaxnreg.inc.sync.aligned.u32 232;");
    uint32_t it = 0;
    for (int i = i0; i < N_ITEMS; i += NCTA) {
      const Item t = get_item(i);
      const int row = t.mb * 128 + wg * 64 + ((tid >> 5) & 3) * 16 + (lane >> 2);
      HPROF(i, 0);
      if (t.type == 2) continue;
      if (t.type == 0) {
        float dg[64], du[64];
#pragma unroll
        for (int j = 0; j < 64; j++) { dg[j] = 0.f; du[j] = 0.f; }
        for (int kb = 0; kb < 10; kb++, it++) {
          const uint32_t st = it % STAGES, base = sb + st * STAGE;
          mbar_wait_long(bar + 8 * st, (it / STAGES) & 1);
          const uint64_t da = mkdesc(base + wg * 8192, 16, 1024, 1), db = mkdesc(base + 16384, 8192, 1024, 1);
          WG_FENCE();
#pragma unroll
          for (int k = 0; k < 4; k++) { wg_ss128<0>(dg, da + 2 * k, db + 128 * k); wg_ss128<0>(du, da + 2 * k, db + 1024 + 128 * k); }
          WG_COMMIT();
          WG_WAIT(1);
          if (kb > 0 && (tid & 127) == 0) mbar_arrive(bar + 64 + 8 * ((it - 1) % STAGES));
        }
        WG_WAIT(0);
        if ((tid & 127) == 0) mbar_arrive(bar + 64 + 8 * ((it - 1) % STAGES));
        uint32_t p[32];
#pragma unroll
        for (int j = 0; j < 32; j++) p[j] = pack2(bfr(dg[2 * j]) * bfr(du[2 * j]), bfr(dg[2 * j + 1]) * bfr(du[2 * j + 1]));
        store_tile(p, sb + OFF_ST + wg * 16384, &tm_hs, t.nt * 128, t.mb * 128 + wg * 64, wg, tid & 127);
        if ((tid & 127) == 0) {
          asm volatile("cp.async.bulk.wait_group 0;" ::: "memory");
          asm volatile("fence.proxy.async;" ::: "memory");
          __threadfence(); atomicAdd(&g_flag[16 + t.mb], 1u);
        }
      } else {
        float d[64];
#pragma unroll
        for (int j = 0; j < 64; j++) d[j] = 0.f;
        uint32_t xr[32];
        {
          const uint32_t* xi = reinterpret_cast<const uint32_t*>(x + (size_t)row * DM + t.nt * 128 + (lane & 3) * 2);
#pragma unroll
          for (int j = 0; j < 16; j++) { xr[2 * j] = __ldg(xi + j * 4); xr[2 * j + 1] = __ldg(xi + j * 4 + 4 * DM); }
        }
        int kb = t.k0;
        for (; kb < t.k1 && kb < 24; kb++, it++) {
          const uint32_t st = it % STAGES, base = sb + st * STAGE;
          mbar_wait_long(bar + 8 * st, (it / STAGES) & 1);
          const uint64_t da = mkdesc(base + wg * 8192, 16, 1024, 1), db = mkdesc(base + 16384, 8192, 1024, 1);
          WG_FENCE();
#pragma unroll
          for (int k = 0; k < 4; k++) wg_ss128<0>(d, da + 2 * k, db + 128 * k);
          WG_COMMIT();
          WG_WAIT(1);
          if (kb > t.k0 && (tid & 127) == 0) mbar_arrive(bar + 64 + 8 * ((it - 1) % STAGES));
        }
        WG_WAIT(0);
        for (; kb < t.k1; kb++, it++) {
          const uint32_t st = it % STAGES, base = sb + st * STAGE;
          mbar_wait_long(bar + 8 * st, (it / STAGES) & 1);
          if (kb == 24 || kb == t.k0) HPROF(i, 1);
          const uint64_t da = mkdesc(base + wg * 8192, 4096, 512, 2), db = mkdesc(base + 16384, 8192, 1024, 1);
          WG_FENCE();
#pragma unroll
          for (int k = 0; k < 4; k++) wg_ss128<1>(d, da + 64 * k, db + 128 * k);
          WG_COMMIT();
          WG_WAIT(1);
          if (kb > t.k0 && (tid & 127) == 0) mbar_arrive(bar + 64 + 8 * ((it - 1) % STAGES));
        }
        WG_WAIT(0);
        if ((tid & 127) == 0) mbar_arrive(bar + 64 + 8 * ((it - 1) % STAGES));
        HPROF(i, 2);
        {
          const uint32_t m = t.k0 == 0 ? 0xffff0000u : 0u;
#pragma unroll
          for (int j = 0; j < 32; j++) { d[2 * j] += __uint_as_float((xr[j] << 16) & m); d[2 * j + 1] += __uint_as_float(xr[j] & m); }
        }
        bool fin = true;
        if (t.nsplit > 1) {
          const int ti = (t.mb - SB0) * 5 + t.nt;
          float4* pp = g_part + ti * 4096 + tid;
#pragma unroll
          for (int j = 0; j < 16; j++) red4(pp + j * 256, d[4 * j], d[4 * j + 1], d[4 * j + 2], d[4 * j + 3]);
          bar_sync(1 + wg, 128);
          volatile unsigned* sflag = reinterpret_cast<volatile unsigned*>(smem + OFF_BAR + 256 + wg * 4);
          if ((tid & 127) == 0) {
            __threadfence();
            const unsigned old = atomicAdd(&g_flag[32 + ti], wg ? 0x10000u : 1u);
            *sflag = ((wg ? old >> 16 : old & 0xffffu) == (unsigned)t.nsplit - 1);
            __threadfence();
          }
          bar_sync(1 + wg, 128);
          fin = __shfl_sync(~0u, *sflag, 0) != 0;
          if (fin) {
#pragma unroll
            for (int j = 0; j < 16; j++) {
              const float4 u = __ldcg(pp + j * 256);
              d[4 * j] = u.x; d[4 * j + 1] = u.y; d[4 * j + 2] = u.z; d[4 * j + 3] = u.w;
            }
          }
        }
        if (fin) {
          uint32_t p[32];
#pragma unroll
          for (int j = 0; j < 32; j++) p[j] = pack2(d[2 * j], d[2 * j + 1]);
          store_tile(p, sb + OFF_ST + wg * 16384, &tm_out, t.nt * 128, t.mb * 128 + wg * 64, wg, tid & 127);
        }
      }
      HPROF(i, 3);
    }
    if ((tid & 127) == 0) asm volatile("cp.async.bulk.wait_group 0;" ::: "memory");
    asm volatile("griddepcontrol.wait;" ::: "memory");
    bar_sync(3, 256);
    if (tid == 0) {
      __threadfence();
      if (atomicAdd(&g_flag[F_DONE], 1u) == NCTA - 1) { for (int j = 0; j < 64; j++) g_flag[j] = 0; }
    }
  }
}

typedef CUresult (*EncodeFn)(CUtensorMap*, CUtensorMapDataType, cuuint32_t, void*, const cuuint64_t*, const cuuint64_t*, const cuuint32_t*,
                             const cuuint32_t*, CUtensorMapInterleave, CUtensorMapSwizzle, CUtensorMapL2promotion, CUtensorMapFloatOOBfill);
static void make_map(EncodeFn enc, CUtensorMap* m, const void* p, int rank, const cuuint64_t* dims, const cuuint64_t* strides,
                     const cuuint32_t* box, CUtensorMapSwizzle swz) {
  cuuint32_t es[3] = {1, 1, 1};
  enc(m, CU_TENSOR_MAP_DATA_TYPE_BFLOAT16, rank, const_cast<void*>(p), dims, strides, box, es, CU_TENSOR_MAP_INTERLEAVE_NONE, swz,
      CU_TENSOR_MAP_L2_PROMOTION_L2_128B, CU_TENSOR_MAP_FLOAT_OOB_FILL_NONE);
}
static void map2d(EncodeFn enc, CUtensorMap* m, const void* p, int cols, int rows, int bc, int br, CUtensorMapSwizzle swz) {
  cuuint64_t dims[2] = {(cuuint64_t)cols, (cuuint64_t)rows}, strides[1] = {(cuuint64_t)cols * 2};
  cuuint32_t box[2] = {(cuuint32_t)bc, (cuuint32_t)br};
  make_map(enc, m, p, 2, dims, strides, box, swz);
}

extern "C" void kernel_launch(void* const* d_in, const int* in_sizes, int n_in, void* d_out, int out_size) {
  const bf16* x = (const bf16*)d_in[0];
  const bf16* mem0 = (const bf16*)d_in[1];
  const bf16* Wq = (const bf16*)d_in[2];
  const bf16* Wk = (const bf16*)d_in[3];
  const bf16* Wv = (const bf16*)d_in[4];
  const bf16* Wo = (const bf16*)d_in[5];
  const bf16* Wg = (const bf16*)d_in[8];
  const bf16* Wu = (const bf16*)d_in[9];
  const bf16* Wd = (const bf16*)d_in[10];
  bf16* out = (bf16*)d_out;

  void* fn = nullptr; cudaDriverEntryPointQueryResult qr;
  cudaGetDriverEntryPoint("cuTensorMapEncodeTiled", &fn, cudaEnableDefault, &qr);
  EncodeFn enc = (EncodeFn)fn;
  void *p_xn, *p_oT, *p_h;
  cudaGetSymbolAddress(&p_xn, g_xn); cudaGetSymbolAddress(&p_oT, g_oT); cudaGetSymbolAddress(&p_h, g_h);

  CUtensorMap t_x32, t_wv, t_wo16, t_x128, t_wg, t_wu, t_h, t_o, t_wd, t_wo64, t_hs, t_out, t_wq, t_wk;
  map2d(enc, &t_wq, Wq, HD, DM, 64, 128, CU_TENSOR_MAP_SWIZZLE_128B);
  map2d(enc, &t_wk, Wk, HD, DM, 64, 128, CU_TENSOR_MAP_SWIZZLE_128B);
  map2d(enc, &t_hs, p_h, FF, SEQ, 64, 64, CU_TENSOR_MAP_SWIZZLE_128B);
  map2d(enc, &t_out, out, DM, SEQ, 64, 64, CU_TENSOR_MAP_SWIZZLE_128B);
  map2d(enc, &t_x32, p_xn, DM, SEQ, 64, 32, CU_TENSOR_MAP_SWIZZLE_128B);
  map2d(enc, &t_wv, Wv, HD, DM, 64, 128, CU_TENSOR_MAP_SWIZZLE_128B);
  map2d(enc, &t_wo16, Wo, DM, HD, 16, 64, CU_TENSOR_MAP_SWIZZLE_32B);
  map2d(enc, &t_x128, p_xn, DM, SEQ, 64, 128, CU_TENSOR_MAP_SWIZZLE_128B);
  map2d(enc, &t_wg, Wg, FF, DM, 64, 64, CU_TENSOR_MAP_SWIZZLE_128B);
  map2d(enc, &t_wu, Wu, FF, DM, 64, 64, CU_TENSOR_MAP_SWIZZLE_128B);
  map2d(enc, &t_h, p_h, FF, SEQ, 64, 128, CU_TENSOR_MAP_SWIZZLE_128B);
  map2d(enc, &t_wd, Wd, DM, FF, 64, 64, CU_TENSOR_MAP_SWIZZLE_128B);
  map2d(enc, &t_wo64, Wo, DM, HD, 64, 64, CU_TENSOR_MAP_SWIZZLE_128B);
  {
    cuuint64_t dims[3] = {32, (cuuint64_t)HD, (cuuint64_t)NSEG}, strides[2] = {64, (cuuint64_t)HD * 64};
    cuuint32_t box[3] = {32, 64, 4};
    make_map(enc, &t_o, p_oT, 3, dims, strides, box, CU_TENSOR_MAP_SWIZZLE_64B);
  }
  cudaFuncSetAttribute(chain_kernel, cudaFuncAttributeMaxDynamicSharedMemorySize, ck::SMEM + CK_EXTRA);
  cudaFuncSetAttribute(helper_kernel, cudaFuncAttributeMaxDynamicSharedMemorySize, hk::SMEM);

  cudaStream_t st = cudaStreamPerThread;
  {
    cudaLaunchConfig_t cfg = {};
    cfg.gridDim = dim3(ck::CL * ck::NCL); cfg.blockDim = dim3(384); cfg.dynamicSmemBytes = ck::SMEM + CK_EXTRA; cfg.stream = st;
    cudaLaunchAttribute at[1];
    at[0].id = cudaLaunchAttributeClusterDimension; at[0].val.clusterDim.x = ck::CL; at[0].val.clusterDim.y = 1; at[0].val.clusterDim.z = 1;
    cfg.attrs = at; cfg.numAttrs = 1;
    cudaLaunchKernelEx(&cfg, chain_kernel, t_x32, t_wv, t_wo16, t_wq, t_wk, mem0, x, 0u);
  }
  {
    cudaLaunchConfig_t cfg = {};
    cfg.gridDim = dim3(hk::NCTA); cfg.blockDim = dim3(384); cfg.dynamicSmemBytes = hk::SMEM; cfg.stream = st;
    cudaLaunchAttribute at[1];
    at[0].id = cudaLaunchAttributeProgrammaticStreamSerialization; at[0].val.programmaticStreamSerializationAllowed = 1;
    cfg.attrs = at; cfg.numAttrs = 1;
    cudaLaunchKernelEx(&cfg, helper_kernel, t_x128, t_wg, t_wu, t_h, t_o, t_wd, t_wo64, t_hs, t_out, x);
  }
}
```

```cpp
#include <cuda_runtime.h>
#include <cuda_bf16.h>
#include <cuda.h>
#include <stdint.h>

typedef __nv_bfloat16 bf16;

constexpr int SEQ = 2048, DM = 640, HD = 6144, FF = 1536, NSEG = 64;
constexpr int ACC_CHUNKS = 1920;

__device__ __align__(1024) bf16 g_xn[SEQ * DM];
__device__ __align__(1024) bf16 g_oT[NSEG * HD * 32];
__device__ __align__(1024) bf16 g_h[SEQ * FF];
__device__ __align__(1024) float4 g_acc[NSEG * ACC_CHUNKS];
__device__ __align__(1024) float4 g_part[20 * 4096];
__device__ unsigned g_flag[64];

__device__ __forceinline__ uint32_t smem_u32(const void* p) { return (uint32_t)__cvta_generic_to_shared(p); }
__device__ __forceinline__ uint32_t mapa(uint32_t a, uint32_t r) { uint32_t o; asm("mapa.shared::cluster.u32 %0, %1, %2;" : "=r"(o) : "r"(a), "r"(r)); return o; }
__device__ __forceinline__ void mbar_init(uint32_t b, int c) { asm volatile("mbarrier.init.shared::cta.b64 [%0], %1;" :: "r"(b), "r"(c) : "memory"); }
__device__ __forceinline__ void mbar_expect(uint32_t b, uint32_t bytes) { asm volatile("mbarrier.arrive.expect_tx.shared::cta.b64 _, [%0], %1;" :: "r"(b), "r"(bytes) : "memory"); }
__device__ __forceinline__ void mbar_arrive(uint32_t b) { asm volatile("mbarrier.arrive.shared::cta.b64 _, [%0];" :: "r"(b) : "memory"); }
constexpr int SPIN_LIMIT = 1 << 20;
__device__ __forceinline__ void mbar_wait(uint32_t b, uint32_t ph) {
  asm volatile("{\n.reg .pred p;\n.reg .u32 n;\nmov.u32 n, 0;\n"
               "W: mbarrier.try_wait.parity.shared::cta.b64 p, [%0], %1;\n@p bra D;\n"
               "add.u32 n, n, 1;\nsetp.lt.u32 p, n, 0x40000;\n@p bra W;\ntrap;\nD:\n}" :: "r"(b), "r"(ph) : "memory");
}
__device__ __forceinline__ void mbar_wait_long(uint32_t b, uint32_t ph) {
  asm volatile("{\n.reg .pred p;\n.reg .u32 n;\nmov.u32 n, 0;\n"
               "W: mbarrier.try_wait.parity.shared::cta.b64 p, [%0], %1;\n@p bra D;\n"
               "add.u32 n, n, 1;\nsetp.lt.u32 p, n, 0x400000;\n@p bra W;\ntrap;\nD:\n}" :: "r"(b), "r"(ph) : "memory");
}
__device__ __forceinline__ void bar_sync(int id, int n) { asm volatile("bar.sync %0, %1;" :: "r"(id), "r"(n) : "memory"); }
__device__ __forceinline__ void bar_arrive(int id, int n) { asm volatile("bar.arrive %0, %1;" :: "r"(id), "r"(n) : "memory"); }
__device__ __forceinline__ void fence_async() { asm volatile("fence.proxy.async.shared::cta;" ::: "memory"); }
__device__ __forceinline__ void cluster_sync() { asm volatile("barrier.cluster.arrive.release.aligned;\nbarrier.cluster.wait.acquire.aligned;" ::: "memory"); }
__device__ __forceinline__ void tma2d(uint32_t dst, const CUtensorMap* m, int c0, int c1, uint32_t bar) {
  asm volatile("cp.async.bulk.tensor.2d.shared::cluster.global.mbarrier::complete_tx::bytes [%0], [%1, {%3, %4}], [%2];"
               :: "r"(dst), "l"(m), "r"(bar), "r"(c0), "r"(c1) : "memory");
}
__device__ __forceinline__ void tma2d_mc(uint32_t dst, const CUtensorMap* m, int c0, int c1, uint32_t bar, uint16_t mask) {
  asm volatile("cp.async.bulk.tensor.2d.shared::cluster.global.mbarrier::complete_tx::bytes.multicast::cluster [%0], [%1, {%3, %4}], [%2], %5;"
               :: "r"(dst), "l"(m), "r"(bar), "r"(c0), "r"(c1), "h"(mask) : "memory");
}
__device__ __forceinline__ void tma3d(uint32_t dst, const CUtensorMap* m, int c0, int c1, int c2, uint32_t bar) {
  asm volatile("cp.async.bulk.tensor.3d.shared::cluster.global.mbarrier::complete_tx::bytes [%0], [%1, {%3, %4, %5}], [%2];"
               :: "r"(dst), "l"(m), "r"(bar), "r"(c0), "r"(c1), "r"(c2) : "memory");
}
__device__ __forceinline__ void st_async1(uint32_t a, uint32_t x, uint32_t mb) {
  asm volatile("st.async.weak.shared::cluster.mbarrier::complete_tx::bytes.b32 [%0], %1, [%2];" :: "r"(a), "r"(x), "r"(mb) : "memory");
}
__device__ __forceinline__ void st_async2(uint32_t a, uint32_t x, uint32_t y, uint32_t mb) {
  asm volatile("st.async.weak.shared::cluster.mbarrier::complete_tx::bytes.v2.b32 [%0], {%1,%2}, [%3];" :: "r"(a), "r"(x), "r"(y), "r"(mb) : "memory");
}
__device__ __forceinline__ void st_async4(uint32_t a, uint32_t x, uint32_t y, uint32_t z, uint32_t w, uint32_t mb) {
  asm volatile("st.async.weak.shared::cluster.mbarrier::complete_tx::bytes.v4.b32 [%0], {%1,%2,%3,%4}, [%5];" :: "r"(a), "r"(x), "r"(y), "r"(z), "r"(w), "r"(mb) : "memory");
}
__device__ __forceinline__ void ldsm4(uint32_t& r0, uint32_t& r1, uint32_t& r2, uint32_t& r3, uint32_t a) {
  asm volatile("ldmatrix.sync.aligned.m8n8.x4.shared.b16 {%0,%1,%2,%3}, [%4];" : "=r"(r0), "=r"(r1), "=r"(r2), "=r"(r3) : "r"(a) : "memory");
}
__device__ __forceinline__ void ldsm4t(uint32_t& r0, uint32_t& r1, uint32_t& r2, uint32_t& r3, uint32_t a) {
  asm volatile("ldmatrix.sync.aligned.m8n8.x4.trans.shared.b16 {%0,%1,%2,%3}, [%4];" : "=r"(r0), "=r"(r1), "=r"(r2), "=r"(r3) : "r"(a) : "memory");
}
__device__ __forceinline__ void stsm4t(uint32_t a, uint32_t r0, uint32_t r1, uint32_t r2, uint32_t r3) {
  asm volatile("stmatrix.sync.aligned.m8n8.x4.trans.shared.b16 [%0], {%1,%2,%3,%4};" :: "r"(a), "r"(r0), "r"(r1), "r"(r2), "r"(r3) : "memory");
}
__device__ __forceinline__ void stsm1t(uint32_t a, uint32_t r0) {
  asm volatile("stmatrix.sync.aligned.m8n8.x1.trans.shared.b16 [%0], {%1};" :: "r"(a), "r"(r0) : "memory");
}
__device__ __forceinline__ void stsm2t(uint32_t a, uint32_t r0, uint32_t r1) {
  asm volatile("stmatrix.sync.aligned.m8n8.x2.trans.shared.b16 [%0], {%1,%2};" :: "r"(a), "r"(r0), "r"(r1) : "memory");
}
__device__ __forceinline__ void mma16816(float* d, uint32_t a0, uint32_t a1, uint32_t a2, uint32_t a3, uint32_t b0, uint32_t b1) {
  asm volatile("mma.sync.aligned.m16n8k16.row.col.f32.bf16.bf16.f32 {%0,%1,%2,%3}, {%4,%5,%6,%7}, {%8,%9}, {%0,%1,%2,%3};"
               : "+f"(d[0]), "+f"(d[1]), "+f"(d[2]), "+f"(d[3]) : "r"(a0), "r"(a1), "r"(a2), "r"(a3), "r"(b0), "r"(b1));
}
__device__ __forceinline__ void mma1688(float* d, uint32_t a0, uint32_t a1, uint32_t b0) {
  asm volatile("mma.sync.aligned.m16n8k8.row.col.f32.bf16.bf16.f32 {%0,%1,%2,%3}, {%4,%5}, {%6}, {%0,%1,%2,%3};"
               : "+f"(d[0]), "+f"(d[1]), "+f"(d[2]), "+f"(d[3]) : "r"(a0), "r"(a1), "r"(b0));
}
__device__ __forceinline__ float ex2(float x) { float r; asm("ex2.approx.ftz.f32 %0, %1;" : "=f"(r) : "f"(x)); return r; }
__device__ __forceinline__ float rcp(float x) { float r; asm("rcp.approx.ftz.f32 %0, %1;" : "=f"(r) : "f"(x)); return r; }
__device__ __forceinline__ uint32_t pack2(float lo, float hi) { uint32_t r; asm("cvt.rn.bf16x2.f32 %0, %1, %2;" : "=r"(r) : "f"(hi), "f"(lo)); return r; }
__device__ __forceinline__ float2 lds2f(uint32_t a) { float2 v; asm volatile("ld.shared.v2.f32 {%0,%1}, [%2];" : "=f"(v.x), "=f"(v.y) : "r"(a) : "memory"); return v; }
__device__ __forceinline__ float4 lds4f(uint32_t a) { float4 v; asm volatile("ld.shared.v4.f32 {%0,%1,%2,%3}, [%4];" : "=f"(v.x), "=f"(v.y), "=f"(v.z), "=f"(v.w) : "r"(a) : "memory"); return v; }
__device__ __forceinline__ uint4 lds4u(uint32_t a) { uint4 v; asm volatile("ld.shared.v4.u32 {%0,%1,%2,%3}, [%4];" : "=r"(v.x), "=r"(v.y), "=r"(v.z), "=r"(v.w) : "r"(a) : "memory"); return v; }
__device__ __forceinline__ float lds1f(uint32_t a) { float v; asm volatile("ld.shared.f32 %0, [%1];" : "=f"(v) : "r"(a) : "memory"); return v; }
__device__ __forceinline__ void sts4f(uint32_t a, float x, float y, float z, float w) { asm volatile("st.shared.v4.f32 [%0], {%1,%2,%3,%4};" :: "r"(a), "f"(x), "f"(y), "f"(z), "f"(w) : "memory"); }
__device__ __forceinline__ void sts2f(uint32_t a, float x, float y) { asm volatile("st.shared.v2.f32 [%0], {%1,%2};" :: "r"(a), "f"(x), "f"(y) : "memory"); }
__device__ __forceinline__ void sts1f(uint32_t a, float x) { asm volatile("st.shared.f32 [%0], %1;" :: "r"(a), "f"(x) : "memory"); }
__device__ __forceinline__ void sts1u(uint32_t a, uint32_t x) { asm volatile("st.shared.u32 [%0], %1;" :: "r"(a), "r"(x) : "memory"); }
__device__ __forceinline__ void sts4u(uint32_t a, uint4 v) { asm volatile("st.shared.v4.u32 [%0], {%1,%2,%3,%4};" :: "r"(a), "r"(v.x), "r"(v.y), "r"(v.z), "r"(v.w) : "memory"); }
__device__ __forceinline__ float4 ld_relaxed4(const float4* p) {
  float4 r; asm volatile("ld.relaxed.gpu.global.v4.f32 {%0,%1,%2,%3}, [%4];" : "=f"(r.x), "=f"(r.y), "=f"(r.z), "=f"(r.w) : "l"(p) : "memory"); return r;
}
__device__ __forceinline__ void red4(float4* p, float a, float b, float c, float d) {
  asm volatile("red.relaxed.gpu.global.add.v4.f32 [%0], {%1,%2,%3,%4};" :: "l"(p), "f"(a), "f"(b), "f"(c), "f"(d) : "memory");
}
__device__ __forceinline__ uint64_t mkdesc(uint32_t addr, uint32_t lbo, uint32_t sbo, uint32_t swz) {
  return (uint64_t)((addr & 0x3FFFF) >> 4) | ((uint64_t)(lbo >> 4) << 16) | ((uint64_t)(sbo >> 4) << 32) | ((uint64_t)swz << 62);
}
#define WG_FENCE() asm volatile("wgmma.fence.sync.aligned;" ::: "memory")
#define WG_COMMIT() asm volatile("wgmma.commit_group.sync.aligned;" ::: "memory")
#define WG_WAIT(n) asm volatile("wgmma.wait_group.sync.aligned %0;" :: "n"(n) : "memory")
#define OPAQUE64(x) asm volatile("" : "+l"(x))

#define F4(d, i) "+f"(d[i]), "+f"(d[i + 1]), "+f"(d[i + 2]), "+f"(d[i + 3])
#define F16(d, i) F4(d, i), F4(d, i + 4), F4(d, i + 8), F4(d, i + 12)
template <int ACC>
__device__ __forceinline__ void wg_rs32(float* d, uint32_t a0, uint32_t a1, uint32_t a2, uint32_t a3, uint64_t b) {
  asm volatile("wgmma.mma_async.sync.aligned.m64n32k16.f32.bf16.bf16 {%0,%1,%2,%3,%4,%5,%6,%7,%8,%9,%10,%11,%12,%13,%14,%15}, {%16,%17,%18,%19}, %20, %21, 1, 1, 0;"
               : F16(d, 0) : "r"(a0), "r"(a1), "r"(a2), "r"(a3), "l"(b), "n"(ACC));
}
template <int ACC>
__device__ __forceinline__ void wg_rs32x(float* d, uint32_t a0, uint32_t a1, uint32_t a2, uint32_t a3, uint32_t blo) {
  asm volatile("{\n.reg .b64 b;\nmov.b64 b, {%20, 0x40000040};\n"
               "wgmma.mma_async.sync.aligned.m64n32k16.f32.bf16.bf16 {%0,%1,%2,%3,%4,%5,%6,%7,%8,%9,%10,%11,%12,%13,%14,%15}, {%16,%17,%18,%19}, b, %21, 1, 1, 0;\n}"
               : F16(d, 0) : "r"(a0), "r"(a1), "r"(a2), "r"(a3), "r"(blo), "n"(ACC));
}
template <int ACC>
__device__ __forceinline__ void wg_rs40(float* d, uint32_t a0, uint32_t a1, uint32_t a2, uint32_t a3, uint64_t b) {
  asm volatile("wgmma.mma_async.sync.aligned.m64n40k16.f32.bf16.bf16 {%0,%1,%2,%3,%4,%5,%6,%7,%8,%9,%10,%11,%12,%13,%14,%15,%16,%17,%18,%19}, {%20,%21,%22,%23}, %24, %25, 1, 1, 0;"
               : F16(d, 0), F4(d, 16) : "r"(a0), "r"(a1), "r"(a2), "r"(a3), "l"(b), "n"(ACC));
}
template <int ACC>
__device__ __forceinline__ void wg_ss8(float* d, uint64_t a, uint64_t b) {
  asm volatile("wgmma.mma_async.sync.aligned.m64n8k16.f32.bf16.bf16 {%0,%1,%2,%3}, %4, %5, %6, 1, 1, 0, 0;" : F4(d, 0) : "l"(a), "l"(b), "n"(ACC));
}
template <int ACC, int TA>
__device__ __forceinline__ void wg_ss40(float* d, uint64_t a, uint64_t b) {
  asm volatile("wgmma.mma_async.sync.aligned.m64n40k16.f32.bf16.bf16 {%0,%1,%2,%3,%4,%5,%6,%7,%8,%9,%10,%11,%12,%13,%14,%15,%16,%17,%18,%19}, %20, %21, %22, 1, 1, %23, 0;"
               : F16(d, 0), F4(d, 16) : "l"(a), "l"(b), "n"(ACC), "n"(TA));
}
template <int TA>
__device__ __forceinline__ void wg_ss128(float* d, uint64_t a, uint64_t b) {
  asm volatile("wgmma.mma_async.sync.aligned.m64n128k16.f32.bf16.bf16 {"
               "%0,%1,%2,%3,%4,%5,%6,%7,%8,%9,%10,%11,%12,%13,%14,%15,%16,%17,%18,%19,%20,%21,%22,%23,%24,%25,%26,%27,%28,%29,%30,%31,"
               "%32,%33,%34,%35,%36,%37,%38,%39,%40,%41,%42,%43,%44,%45,%46,%47,%48,%49,%50,%51,%52,%53,%54,%55,%56,%57,%58,%59,%60,%61,%62,%63"
               "}, %64, %65, 1, 1, 1, %66, 1;"
               : F16(d, 0), F16(d, 16), F16(d, 32), F16(d, 48) : "l"(a), "l"(b), "n"(TA));
}

__device__ __forceinline__ float bfr(float x) { return __bfloat162float(__float2bfloat16_rn(x)); }
constexpr int F_LN = 52, F_DONE = 53, F_W = 54, NHELP = 36;
__device__ __forceinline__ void ln_row(const uint2 (&u)[5], int row, int lane) {
  float v[20];
#pragma unroll
  for (int i = 0; i < 5; i++) {
    v[4 * i + 0] = __uint_as_float(u[i].x << 16); v[4 * i + 1] = __uint_as_float(u[i].x & 0xffff0000u);
    v[4 * i + 2] = __uint_as_float(u[i].y << 16); v[4 * i + 3] = __uint_as_float(u[i].y & 0xffff0000u);
  }
  float s = 0.f;
#pragma unroll
  for (int i = 0; i < 20; i++) s += v[i];
#pragma unroll
  for (int o = 16; o; o >>= 1) s += __shfl_xor_sync(~0u, s, o);
  const float mean = s * (1.0f / DM);
  float q = 0.f;
#pragma unroll
  for (int i = 0; i < 20; i++) { float d = v[i] - mean; q += d * d; }
#pragma unroll
  for (int o = 16; o; o >>= 1) q += __shfl_xor_sync(~0u, q, o);
  const float mb = bfr(mean), rs = 1.0f / bfr(sqrtf(bfr(bfr(q * (1.0f / DM)) + 1e-5f)));
  uint2* dst = reinterpret_cast<uint2*>(g_xn + (size_t)row * DM);
#pragma unroll
  for (int i = 0; i < 5; i++) {
    uint2 o;
    o.x = pack2(bfr(v[4 * i + 0] - mb) * rs, bfr(v[4 * i + 1] - mb) * rs);
    o.y = pack2(bfr(v[4 * i + 2] - mb) * rs, bfr(v[4 * i + 3] - mb) * rs);
    dst[i * 32 + lane] = o;
  }
}
__device__ __forceinline__ void wait_flag(const unsigned* f, unsigned target) {
  unsigned v; int n = 0;
  while (true) {
    asm volatile("ld.acquire.gpu.global.u32 %0, [%1];" : "=r"(v) : "l"(f) : "memory");
    if (v >= target) break;
    if (++n > (1 << 21)) __trap();
    __nanosleep(100);
  }
  asm volatile("fence.proxy.async.global;" ::: "memory");
}

namespace ck {
constexpr int CL = 6, NCL = 16, NRF = 8, NSS = 40 - NRF, NTP = 1;
constexpr uint32_t OFF_H = 0, OFF_WV = 51200, OFF_WO = OFF_WV + NSS * 2048, OFF_Q = OFF_WO + 86016, OFF_K = OFF_Q + 5120,
                   OFF_OG = OFF_K + 5120, OFF_RA = OFF_OG + 6144, OFF_P = OFF_RA + 3840, OFF_RT = OFF_P + 3200,
                   OFF_BAR = OFF_RT + 5120, SMEM = OFF_BAR + 256;
constexpr uint32_t B_X = 0, B_A = 8, B_T = 16, B_W = 24, B_WR = 32, B_B = 40  , B_XF = 88, B_DUMMY = 96, B_WO = 104,
                   B_ST = 128  ;
enum { NB_M = 1, NB_QK = 2, NB_PM = 3, NB_V = 4, NB_TS = 5, NB_P = 6, NB_G = 7, NB_R = 8  , NB_S = 12, NB_V2 = 13 };
static_assert(SMEM <= 232448, "smem");
static_assert(OFF_WO % 1024 == 0 && OFF_Q % 1024 == 0, "align");
}
__device__ __forceinline__ uint32_t opq(uint32_t x) { asm volatile("" : "+r"(x)); return x; }

__device__ __forceinline__ uint32_t memrow_addr(uint32_t sb, uint32_t col0, uint32_t m) {
  return sb + ck::OFF_H + (col0 >> 6) * 5120 + 4096 + m * 128 + ((((col0 >> 3) & 7) ^ m) << 4);
}
constexpr int VLEAD = 5;
constexpr int LW = 24;
constexpr int DEPTH = 2;
template <int N> struct MemLoad { float4 c[N]; };
template <int N>
__device__ __forceinline__ void memload_issue(MemLoad<N>& m, int s, uint32_t warp, uint32_t lane) {
  const float4* p = g_acc + (s * ACC_CHUNKS + warp * 160) + lane;
#pragma unroll
  for (int q = 0; q < N; q++) m.c[q] = ld_relaxed4(p + q * 32);
}
template <int N>
__device__ __forceinline__ void memload_finish(MemLoad<N>& m, int s, uint32_t warp, uint32_t lane0, uint32_t sb, float full) {
  const uint32_t lane = opq(lane0);
  const uint32_t a4 = memrow_addr(sb, warp * 48 + (lane >> 3) * 8, lane & 7), a2 = memrow_addr(sb, warp * 48 + 32 + ((lane >> 3) & 1) * 8, lane & 7);
  const uint32_t a1 = memrow_addr(sb, 576 + warp * 8, lane & 7);
  int n = 0;
  while (true) {
    bool ok = true;
#pragma unroll
    for (int q = 0; q < N; q++) ok = ok && m.c[q].w == full;
    if (__all_sync(~0u, ok)) break;
    if (++n > SPIN_LIMIT) __trap();
    memload_issue(m, s, warp, opq(lane0));
  }
  const float4* c = m.c;
  stsm4t(a4, pack2(c[0].x, c[1].x), pack2(c[2].x, c[3].x), pack2(c[0].y, c[1].y), pack2(c[2].y, c[3].y));
  stsm2t(a2, pack2(c[0].z, c[1].z), pack2(c[2].z, c[3].z));
  if (N == 5) stsm1t(a1, pack2(c[N - 1].x, c[N - 1].y + c[N - 1].z));
}
#define WO_PREFETCH() _Pragma("unroll") for (int i = 0; i < 6; i++) \
  ldsm4t(f[i / 3][4 * (i % 3)], f[i / 3][4 * (i % 3) + 1], f[i / 3][4 * (i % 3) + 2], f[i / 3][4 * (i % 3) + 3], wo + (i % 3) * 12288 + (i / 3) * 2048)
#define HOFF(k) ((uint64_t)((((k) >> 2) * 5120 + ((k) & 3) * 32) >> 4))

template <bool LOADS>
__device__ __forceinline__ void token_qk(const uint32_t* a, int s, uint32_t sb, uint32_t warp, uint32_t lane0, uint32_t zero) {
  using namespace ck;
  const uint32_t bar = sb + OFF_BAR;
  float d[16];
  MemLoad<5> ml;
  mbar_wait(bar + B_X, (s + 1) & 1);
  const uint32_t db = opq((uint32_t)mkdesc(sb + OFF_H, 16, 1024, 1));
  WG_FENCE();
  wg_rs32x<0>(d, a[0], a[1], a[2], a[3], db);
#pragma unroll
  for (int k = 1; k < 40; k++) {
    wg_rs32x<1>(d, a[4 * k], a[4 * k + 1], a[4 * k + 2], a[4 * k + 3], db + (uint32_t)HOFF(k));
    if (LOADS && k == LW) WG_COMMIT();
  }
  WG_COMMIT();
  if (LOADS) { WG_WAIT(1); do { memload_issue(ml, s, warp, opq(lane0)); } while (zero >> 31); }
  WG_WAIT(0);
  const uint32_t e0 = pack2(d[0], d[1]);
  const uint32_t lane = opq(lane0), wg = warp >> 2, w4 = warp & 3;
  const uint32_t mat = lane >> 3, i = lane & 7, h = mat & 1, j0 = mat >> 1;
  const uint32_t ep0 = sb + OFF_Q + wg * 5120 + (8 * j0 + i) * 128 + (((2 * w4 + h) ^ i) << 4), ep1 = ep0 + 2048;
  stsm4t(ep0, e0, pack2(d[2], d[3]), pack2(d[4], d[5]), pack2(d[6], d[7]));
  stsm4t(ep1, pack2(d[8], d[9]), pack2(d[10], d[11]), pack2(d[12], d[13]), pack2(d[14], d[15]));
  if (LOADS) memload_finish(ml, s, warp, lane, sb, __uint_as_float(__float_as_uint((float)NCL) + (e0 & zero)));
}

__global__ void __launch_bounds__(384, 1)
chain_kernel(const __grid_constant__ CUtensorMap tm_x, const __grid_constant__ CUtensorMap tm_wv, const __grid_constant__ CUtensorMap tm_wo,
             const __grid_constant__ CUtensorMap tm_wq, const __grid_constant__ CUtensorMap tm_wk, const bf16* __restrict__ mem0,
             const bf16* __restrict__ x, uint32_t zero) {
  using namespace ck;
  extern __shared__ __align__(1024) unsigned char smem[];
  const uint32_t sb = smem_u32(smem);
  const uint32_t tid0 = threadIdx.x;
  const uint32_t warp = __shfl_sync(~0u, threadIdx.x >> 5, 0);
  const int rank = blockIdx.x % CL, cluster = blockIdx.x / CL;
  const int hb = (rank / 3) * 3, j3 = rank % 3;
  const uint32_t bar = sb + OFF_BAR;

  asm volatile("griddepcontrol.launch_dependents;");
  const int gw = (tid0 >> 5) * 96 + blockIdx.x;
  uint2 xu[2][5];
  uint4 m0u[5];
#pragma unroll
  for (int r = 0; r < 5; r++) m0u[r] = __ldg(reinterpret_cast<const uint4*>(mem0) + (tid0 & 127) + r * 128);
#pragma unroll
  for (int r = 0; r < 2; r++) {
    const int row = min(gw + r * 1152, SEQ - 1);
#pragma unroll
    for (int j = 0; j < 5; j++) xu[r][j] = __ldg(reinterpret_cast<const uint2*>(x + (size_t)row * DM) + j * 32 + (tid0 & 31));
  }
  if (tid0 == 0) {
    mbar_init(bar + B_X, 1); mbar_init(bar + B_A, 1); mbar_init(bar + B_T, 1); mbar_init(bar + B_W, 1); mbar_init(bar + B_WR, 1);
    for (int i = 0; i < 3; i++) mbar_init(bar + B_B + 8 * i, 1);
    for (int i = 0; i < 10; i++) mbar_init(bar + B_ST + 8 * i, 1);
    mbar_init(bar + B_XF, 1); mbar_init(bar + B_WO, 1);
    asm volatile("fence.mbarrier_init.release.cluster;" ::: "memory");
    mbar_expect(bar + B_A, 3 * 1024); mbar_expect(bar + B_T, 2 * 2560);
    for (int i = 0; i < 3; i++) mbar_expect(bar + B_B + 8 * i, 2048);
    for (int i = 0; i < 10; i++) mbar_expect(bar + B_ST + 8 * i, 16384);
    mbar_expect(bar + B_XF, CL * 4);
    mbar_expect(bar + B_X, 40960);
    mbar_expect(bar + B_WR, NRF * 2048);
    mbar_expect(bar + B_W, NSS * 2048); mbar_expect(bar + B_WO, (rank < 4 ? 7 : 6) * 12288);
    tma2d(sb + OFF_H, &tm_wv, blockIdx.x * 64, NSS * 16, bar + B_WR);
  }
  {
    const float4 z = make_float4(0.f, 0.f, 0.f, 0.f);
    for (int j = blockIdx.x * 384 + tid0; j < NSEG * ACC_CHUNKS; j += 96 * 384) g_acc[j] = z;
    for (int j = blockIdx.x * 384 + tid0; j < 20 * 4096; j += 96 * 384) g_part[j] = z;
  }
#pragma unroll 1
  for (int r = 0; r < 2; r++) {
    if (gw + r * 1152 < SEQ) ln_row(xu[0], gw + r * 1152, tid0 & 31);
#pragma unroll
    for (int j = 0; j < 5; j++) xu[0][j] = xu[1][j];
    if (r == 0 && tid0 < 2 * DEPTH) {
      const uint32_t wg = tid0 & 1, i = tid0 >> 1;
      tma2d(sb + (wg == 0 ? OFF_WO + i * 16384 : i < 4 ? OFF_WV + i * 16384 : OFF_Q), wg == 0 ? &tm_wq : &tm_wk, blockIdx.x * 64, i * 128,
            bar + B_ST + 8 * (wg * 5 + i));
    }
    __syncwarp();
  }
  __threadfence();
  __syncthreads();
  if (tid0 == 320) atomicAdd(&g_flag[F_LN], 1u);

  if (warp < 8) {
    asm volatile("setmaxnreg.inc.sync.aligned.u32 208;");
    const uint32_t lane0 = __shfl_sync(~0u, opq(threadIdx.x & 31), threadIdx.x & 31);
    uint32_t a[160];
    {
      const uint32_t wg = warp >> 2, l7 = lane0 & 7, l3 = lane0 >> 3, t128 = tid0 & 127;
      const uint32_t lo = ((l3 >> 1) * 8 + l7) * 128 + (((2 * (warp & 3) + (l3 & 1)) ^ l7) << 4);
#pragma unroll
      for (int i = 0; i < 5; i++) {
        const uint32_t base = sb + (wg == 0 ? OFF_WO + i * 16384 : i < 4 ? OFF_WV + i * 16384 : OFF_Q) + lo;
        mbar_wait(bar + B_ST + 8 * (wg * 5 + i), 0);
        if (i + DEPTH < 5 && t128 == 0)
          tma2d(sb + (wg == 0 ? OFF_WO + (i + DEPTH) * 16384 : i + DEPTH < 4 ? OFF_WV + (i + DEPTH) * 16384 : OFF_Q), wg == 0 ? &tm_wq : &tm_wk,
                blockIdx.x * 64, (i + DEPTH) * 128, bar + B_ST + 8 * (wg * 5 + i + DEPTH));
        __syncwarp();
#pragma unroll
        for (int k = 0; k < 8; k++) ldsm4t(a[32 * i + 4 * k], a[32 * i + 4 * k + 1], a[32 * i + 4 * k + 2], a[32 * i + 4 * k + 3], base + k * 2048);
        asm volatile("" :: "r"(a[32 * i]), "r"(a[32 * i + 4]), "r"(a[32 * i + 8]), "r"(a[32 * i + 12]), "r"(a[32 * i + 16]), "r"(a[32 * i + 20]), "r"(a[32 * i + 24]), "r"(a[32 * i + 28]) : "memory");
        bar_sync(NB_R + wg, 128);
        if (wg == 1) {
          if (i >= 3 && t128 < 2) tma2d(sb + OFF_WV + ((i - 3) * 2 + t128) * 16384, &tm_wv, blockIdx.x * 64, ((i - 3) * 2 + t128) * 128, bar + B_W);
        } else if (i == 4) {
          const int t = t128 / 6, d = t128 % 6;
          if (t < (rank < 4 ? 7 : 6)) tma2d(sb + OFF_WO + t * 12288 + d * 2048, &tm_wo, t < 6 ? rank * 96 + t * 16 : 576 + rank * 16,
                                            cluster * 384 + ((rank + CL - d) % CL) * 64, bar + B_WO);
        }
        __syncwarp();
      }
      bar_sync(NB_QK, 256);
      asm volatile("barrier.cluster.arrive.relaxed.aligned;" ::: "memory");
    }
    token_qk<false>(a, -1, sb, warp, lane0, zero);
    asm volatile("barrier.cluster.wait.acquire.aligned;" ::: "memory");
    const float sc = 0.07216878364870322f * 1.4426950408889634f;

    for (int s = 0;; s++) {
      uint32_t lane;
      {
        const uint32_t ln = opq(lane0);
        const uint32_t x0 = sb + OFF_H + 4096 + (ln & 7) * 128 + (((ln >> 3) ^ (ln & 7)) << 4), x1 = x0 ^ 64;
        float c[16];
#pragma unroll
        for (int i = 0; i < 16; i++) c[i] = 0.f;
        uint32_t bf[1][16];
        bar_sync(NB_M, 384);
#pragma unroll
        for (int k = 0; k < 40; k += 2) {
          uint32_t* b = bf[0] + 12;
          ldsm4(b[0], b[1], b[2], b[3], ((k & 2) ? x1 : x0) + (k >> 2) * 5120);
          float* d = c + ((k & 2) ? 8 : 0);
          mma16816(d, a[4 * k], a[4 * k + 1], a[4 * k + 2], a[4 * k + 3], b[0], b[1]);
          mma16816(d + 4, a[4 * k + 4], a[4 * k + 5], a[4 * k + 6], a[4 * k + 7], b[2], b[3]);
        }
#pragma unroll
        for (int i = 0; i < 4; i++) c[i] = (c[i] + c[4 + i]) + (c[8 + i] + c[12 + i]);
        asm volatile("add.u32 %0, %1, %2;" : "=r"(lane) : "r"(lane0), "r"(bf[0][15] & zero));
        const uint32_t qst = sb + OFF_Q + (warp >> 2) * 5120 + (32 + (lane & 7)) * 128 + (((2 * (warp & 3) + ((lane >> 3) & 1)) ^ (lane & 7)) << 4);
        stsm2t(qst, pack2(c[0], c[1]), pack2(c[2], c[3]));
      }
      const uint32_t l7 = lane & 7, l3 = lane >> 3;
      fence_async();
      bar_arrive(NB_S, 384);
      if (s == NSEG - 1) break;
      if (s == 0) { mbar_wait(bar + B_WO, 0); if (tid0 == 64) atomicAdd(&g_flag[F_W], 1u); }
      const uint32_t grp = warp >> 2, kq = warp & 3;
      const uint32_t wo = sb + OFF_WO + grp * 36864 + kq * 512 + ((l3 >> 1) * 8 + l7) * 32 + (((l3 & 1) ^ (kq >> 1) ^ (l7 >> 2)) << 4);
      uint32_t f[2][12];
      if (warp >= 5) {
        const uint32_t g = warp - 5;
        const uint32_t r4 = sb + OFF_RA + g * 256 + (l3 >> 1) * 1024 + (lane & 15) * 16, r2 = sb + OFF_RA + g * 256 + 2048 + (lane & 15) * 16;
        mbar_wait(bar + B_A, s & 1);
        uint32_t t0, t1, t2, t3, t4, t5;
        ldsm4t(t0, t1, t2, t3, r4);
        asm volatile("ldmatrix.sync.aligned.m8n8.x2.trans.shared.b16 {%0,%1}, [%2];" : "=r"(t4), "=r"(t5) : "r"(r2) : "memory");
        float p0 = (__uint_as_float(t0 << 16) + __uint_as_float(t2 << 16)) + __uint_as_float(t4 << 16);
        float p1 = (__uint_as_float(t0 & 0xffff0000u) + __uint_as_float(t2 & 0xffff0000u)) + __uint_as_float(t4 & 0xffff0000u);
        float p2 = (__uint_as_float(t1 << 16) + __uint_as_float(t3 << 16)) + __uint_as_float(t5 << 16);
        float p3 = (__uint_as_float(t1 & 0xffff0000u) + __uint_as_float(t3 & 0xffff0000u)) + __uint_as_float(t5 & 0xffff0000u);
        if (g == 2) { p2 = -INFINITY; p3 = -INFINITY; }
        float mx = fmaxf(fmaxf(p0, p1), fmaxf(p2, p3));
        mx = fmaxf(mx, __shfl_xor_sync(~0u, mx, 1)); mx = fmaxf(mx, __shfl_xor_sync(~0u, mx, 2));
        mx *= sc;
        const uint32_t e0 = pack2(ex2(fmaf(p0, sc, -mx)), ex2(fmaf(p1, sc, -mx))), e1 = pack2(ex2(fmaf(p2, sc, -mx)), ex2(fmaf(p3, sc, -mx)));
        const uint32_t pw = sb + OFF_P + lane * 16;
        sts1u(pw + (g == 2 ? 512 : g * 4), e0);
        sts1u(pw + (g == 2 ? 1024 : 8 + g * 4), e1);
        sts1f(pw + 516 + g * 4, mx);
        bar_arrive(NB_PM, 224);
      }
      if (warp == 1 || warp == 2) {
        const uint32_t rb = mapa(sb, lane < CL ? lane : 0);
        bar_sync(NB_V2, 192);
        if (warp == 1 && lane < CL) st_async1(rb + OFF_BAR + B_DUMMY, 0u, rb + OFF_BAR + B_XF);
        if (warp == 2) {
          if (lane == 0) mbar_expect(bar + B_X, 40960);
          mbar_wait(bar + B_XF, s & 1);
          if (lane == 0) mbar_expect(bar + B_XF, CL * 4);
          const int c2 = rank + 6 * lane;
          if (c2 < 10) tma2d_mc(sb + OFF_H + c2 * 5120, &tm_x, c2 * 64, (s + 1) * 32, bar + B_X, (uint16_t)0x3f);
          __syncwarp();
        }
      }
      {
        const uint32_t og = sb + OFF_OG + kq * 256 + (lane ^ ((kq & 1) << 2)) * 8;
        float v[12];
#pragma unroll
        for (int i = 0; i < 12; i++) v[i] = 0.f;
        bar_sync(NB_V, 384);
        WO_PREFETCH();
        bar_sync(NB_TS, 384);
#pragma unroll
        for (int u = 0; u < 3; u++) {
          mbar_wait(bar + B_B + 8 * u, s & 1);
          const float2 o0 = lds2f(og + u * 2048), o1 = lds2f(og + u * 2048 + 1024);
#pragma unroll
          for (int h = 0; h < 2; h++) {
            uint32_t* ff = f[h];
#pragma unroll
            for (int i = 0; i < 3; i++)
              mma16816(v + 4 * i, ff[4 * i], ff[4 * i + 1], ff[4 * i + 2], ff[4 * i + 3], __float_as_uint(h ? o1.x : o0.x), __float_as_uint(h ? o1.y : o0.y));
            if (u < 2) {
#pragma unroll
              for (int i = 0; i < 3; i++) ldsm4t(ff[4 * i], ff[4 * i + 1], ff[4 * i + 2], ff[4 * i + 3], wo + (2 * u + 2 + h) * 2048 + i * 12288);
            }
          }
        }
        const uint32_t xb = sb + OFF_Q + grp * 4608;
#pragma unroll
        for (int i = 1; i < 4; i++) {
          const uint32_t x = xb + ((i ^ kq) * 3 + (i - 1)) * 384;
          sts2f(x + lane * 8, v[i], v[4 + i]); sts1f(x + 256 + lane * 4, v[8 + i]);
        }
        float4* o = g_acc + (s * ACC_CHUNKS + (2 * rank + grp) * 160 + kq * 32) + lane;
        const uint32_t y = xb + kq * 1152;
        bar_sync(NB_R + grp, 128);
        const float2 p0 = lds2f(y + lane * 8), p1 = lds2f(y + 384 + lane * 8), p2 = lds2f(y + 768 + lane * 8);
        const float q0 = lds1f(y + 256 + lane * 4), q1 = lds1f(y + 640 + lane * 4), q2 = lds1f(y + 1024 + lane * 4);
        red4(o, (v[0] + p0.x) + (p1.x + p2.x), (v[4] + p0.y) + (p1.y + p2.y), (v[8] + q0) + (q1 + q2), 1.0f);
      }
      bar_sync(NB_G, 384);
      token_qk<true>(a, s, sb, warp, lane0, zero);
    }
    cluster_sync();
  } else {
    asm volatile("setmaxnreg.dec.sync.aligned.u32 88;");
    const uint32_t lane0 = __shfl_xor_sync(~0u, opq((threadIdx.x & 31) ^ 1), 1);
    asm volatile("barrier.cluster.arrive.relaxed.aligned;" ::: "memory");
    uint32_t wv[4 * NRF];
    {
      const int i = tid0 - 256;
      mbar_wait(bar + B_WR, 0);
      const uint32_t l7 = lane0 & 7, l3 = lane0 >> 3;
#pragma unroll
      for (int k = 0; k < NRF; k++)
        ldsm4t(wv[4 * k], wv[4 * k + 1], wv[4 * k + 2], wv[4 * k + 3], sb + OFF_H + k * 2048 + ((l3 >> 1) * 8 + l7) * 128 + (((2 * (warp - 8) + (l3 & 1)) ^ l7) << 4));
      asm volatile("" :: "r"(wv[0]), "r"(wv[4]), "r"(wv[8]), "r"(wv[12]), "r"(wv[16]), "r"(wv[20]), "r"(wv[24]), "r"(wv[28]) : "memory");
      bar_sync(NB_P, 128);
#pragma unroll
      for (int r = 0; r < 5; r++) { const uint32_t j = i + r * 128; sts4u(memrow_addr(sb, (j % 80) * 8, j / 80), m0u[r]); }
      fence_async();
      if (i == 96) {
        wait_flag(&g_flag[F_LN], 96);
        for (int c = 0; c < 10; c++) tma2d(sb + OFF_H + c * 5120, &tm_x, c * 64, 0, bar + B_X);
      }
      __syncwarp();
    }
    mbar_wait(bar + B_W, 0);
    asm volatile("barrier.cluster.wait.acquire.aligned;" ::: "memory");
    const float sc = 0.07216878364870322f * 1.4426950408889634f;

    bar_arrive(NB_M, 384);
    for (int s = 0; s < NSEG; s++) {
      const bool last = s == NSEG - 1;
      uint32_t va[10];
      {
        uint32_t wt_[4 * NTP];
        {
          const uint32_t ln = opq(lane0), l7 = ln & 7, l3 = ln >> 3;
#pragma unroll
          for (int k = 0; k < NTP; k++)
            ldsm4t(wt_[4 * k], wt_[4 * k + 1], wt_[4 * k + 2], wt_[4 * k + 3],
                   sb + OFF_WV + (NSS - NTP + k) * 2048 + ((l3 >> 1) * 8 + l7) * 128 + (((2 * (warp - 8) + (l3 & 1)) ^ l7) << 4));
        }
        mbar_wait(bar + B_X, s & 1);
        float v[20];
        uint64_t db = mkdesc(sb + OFF_H, 16, 1024, 1), da = mkdesc(sb + OFF_WV, 1024, 1024, 1);
        OPAQUE64(db); OPAQUE64(da);
        uint64_t dk = mkdesc(sb + OFF_K, 16, 1024, 1), dq = mkdesc(sb + OFF_Q + 4096, 16, 1024, 1);
        OPAQUE64(dk); OPAQUE64(dq);
        const uint32_t ra = OFF_RA + j3 * 1024 + (warp - 8) * 256 + opq(lane0) * 4;
        float sm[4];
        bar_sync(NB_S, 384);
        WG_FENCE();
        wg_ss8<0>(sm, dk, dq); wg_ss8<1>(sm, dk + 2, dq + 2); wg_ss8<1>(sm, dk + 4, dq + 4); wg_ss8<1>(sm, dk + 6, dq + 6);
        WG_COMMIT();
        wg_ss40<0, 1>(v, da, db);
#pragma unroll
        for (int k = 1; k < VLEAD; k++) wg_ss40<1, 1>(v, da + (uint64_t)(k * 128), db + HOFF(k));
        WG_COMMIT();
        WG_WAIT(1);
        {
          const uint32_t x = pack2(sm[0], sm[1]), y = pack2(sm[2], sm[3]);
#pragma unroll
          for (int d = 0; d < 3; d++) {
            const uint32_t rb = mapa(sb, hb + (j3 + 1 + d) % 3);
            st_async1(rb + ra, x, rb + OFF_BAR + B_A); st_async1(rb + ra + 128, y, rb + OFF_BAR + B_A);
          }
        }
#pragma unroll
        for (int k = VLEAD; k < NSS - NTP; k++) wg_ss40<1, 1>(v, da + (uint64_t)(k * 128), db + HOFF(k));
#pragma unroll
        for (int k = 0; k < NTP; k++) wg_rs40<1>(v, wt_[4 * k], wt_[4 * k + 1], wt_[4 * k + 2], wt_[4 * k + 3], db + HOFF(NSS - NTP + k));
#pragma unroll
        for (int k = NSS; k < 40; k++) wg_rs40<1>(v, wv[4 * (k - NSS)], wv[4 * (k - NSS) + 1], wv[4 * (k - NSS) + 2], wv[4 * (k - NSS) + 3], db + HOFF(k));
        WG_COMMIT();
        WG_WAIT(0);
#pragma unroll
        for (int i = 0; i < 10; i++) va[i] = pack2(v[2 * i], v[2 * i + 1]);
      }
      const uint32_t lane = opq(lane0), w4 = warp - 8, wt = w4 * 32 + lane;
      if (!last) {
        bar_arrive(NB_V2, 192);
        bar_sync(NB_PM, 224);
        const uint4 pa = lds4u(sb + OFF_P + lane * 16), pc = lds4u(sb + OFF_P + 512 + lane * 16);
        float o[6][4], os[4], ot[4];
#pragma unroll
        for (int i = 0; i < 4; i++) { o[0][i] = o[1][i] = o[2][i] = o[3][i] = o[4][i] = o[5][i] = os[i] = ot[i] = 0.f; }
        mma16816(os, pa.x, pa.y, pa.z, pa.w, 0x3f803f80u, 0x3f803f80u);
        mma1688(ot, pc.x, pc.y, 0x3f803f80u);
        mma16816(o[0], pa.x, pa.y, pa.z, pa.w, va[0], va[2]);
        mma16816(o[1], pa.x, pa.y, pa.z, pa.w, va[1], va[3]);
        mma16816(o[2], pa.x, pa.y, pa.z, pa.w, va[4], va[6]);
        mma16816(o[3], pa.x, pa.y, pa.z, pa.w, va[5], va[7]);
        mma1688(o[4], pc.x, pc.y, va[8]);
        mma1688(o[5], pc.x, pc.y, va[9]);
        o[2][0] = o[2][2]; o[2][1] = o[2][3]; o[3][0] = o[3][2]; o[3][1] = o[3][3];
        const float ma = __uint_as_float(pc.y), mb = __uint_as_float(pc.z), mc = __uint_as_float(pc.w), mx = fmaxf(fmaxf(ma, mb), mc);
        float fa = ex2(ma - mx), fb = ex2(mb - mx), fc = ex2(mc - mx);
        const float inv = rcp(fmaf(fa, os[0], fmaf(fb, os[2], fc * ot[0])));
        fa *= inv; fb *= inv; fc *= inv;
        const uint32_t x = pack2(fmaf(fa, o[0][0], fmaf(fb, o[2][0], fc * o[4][0])), fmaf(fa, o[0][1], fmaf(fb, o[2][1], fc * o[4][1])));
        const uint32_t y = pack2(fmaf(fa, o[1][0], fmaf(fb, o[3][0], fc * o[5][0])), fmaf(fa, o[1][1], fmaf(fb, o[3][1], fc * o[5][1])));
#pragma unroll
        for (int d = 0; d < CL; d++) {
          int r = rank + d; if (r >= CL) r -= CL;
          const uint32_t rb = mapa(sb, r);
          st_async2(rb + OFF_OG + wt * 8 + d * 1024, x, y, rb + OFF_BAR + B_B + 8 * (d >> 1));
        }
        bar_arrive(NB_V, 384);
        if (wt == 0) mbar_expect(bar + B_A, 3 * 1024);
      }
      uint32_t e[5];
      {
        float v[20];
        uint64_t da = mkdesc(sb + OFF_Q, 16, 512, 1), db = mkdesc(sb + OFF_K, 16, 1024, 1);
        OPAQUE64(db); OPAQUE64(da);
        WG_FENCE();
        wg_ss40<0, 0>(v, da, db);
        wg_ss40<1, 0>(v, da + 2, db + 2);
        wg_ss40<1, 0>(v, da + 4, db + 4);
        wg_ss40<1, 0>(v, da + 6, db + 6);
        WG_COMMIT();
        WG_WAIT(0);
#pragma unroll
        for (int i = 0; i < 5; i++) e[i] = pack2(v[4 * i], v[4 * i + 1]);
      }
      if (!last) {
        bar_arrive(NB_TS, 384);
        if (w4 == 3) {
          if ((s & 3) == 0 && s > 0 && lane == 0) { __threadfence(); atomicAdd(&g_flag[(s >> 2) - 1], 1u); }
          __syncwarp();
        } else if (w4 != 0 && rank < 4) {
          if (s == 0) mbar_wait(bar + B_WO, 0);
          const uint32_t kh = w4 - 1, l7 = lane & 7, l3 = lane >> 3;
          const uint32_t wo = sb + OFF_WO + 6 * 12288 + kh * 2048 + ((l3 >> 1) * 8 + l7) * 32 + (((l3 & 1) ^ (l7 >> 2)) << 4);
          const uint32_t og = sb + OFF_OG + kh * 1024 + lane * 8;
          float u[4] = {0.f, 0.f, 0.f, 0.f};
#pragma unroll
          for (int it = 0; it < 3; it++) {
            uint32_t ff[16];
#pragma unroll
            for (int kk = 0; kk < 4; kk++) ldsm4t(ff[4 * kk], ff[4 * kk + 1], ff[4 * kk + 2], ff[4 * kk + 3], wo + it * 4096 + kk * 512);
            mbar_wait(bar + B_B + 8 * it, s & 1);
#pragma unroll
            for (int kk = 0; kk < 4; kk++) {
              const float2 o = lds2f(og + it * 2048 + kk * 256);
              mma16816(u, ff[4 * kk], ff[4 * kk + 1], ff[4 * kk + 2], ff[4 * kk + 3], __float_as_uint(o.x), __float_as_uint(o.y));
            }
          }
          const uint32_t xb = sb + OFF_RA + lane * 8;
          sts2f(xb + kh * 256, kh ? u[0] : u[2], kh ? u[1] : u[3]);
          float4* o = g_acc + (s * ACC_CHUNKS + (2 * rank + kh) * 160 + 128) + lane;
          bar_sync(NB_R + 2, 64);
          const float2 x = lds2f(xb + 256 - kh * 256);
          red4(o, (kh ? u[2] : u[0]) + x.x, (kh ? u[3] : u[1]) + x.y, 0.f, 1.0f);
        }
        bar_sync(NB_G, 384);
        if (wt < 3) mbar_expect(bar + B_B + 8 * wt, 2048);
      } else {
        mbar_wait(bar + B_A, s & 1);
      }
      {
#pragma unroll
        for (int d = 1; d <= 2; d++) {
          const uint32_t rb = mapa(sb, hb + (j3 + d) % 3);
          st_async4(rb + OFF_RT + (2 - d) * 2560 + wt * 16, e[0], e[1], e[2], e[3], rb + OFF_BAR + B_T);
          st_async1(rb + OFF_RT + (2 - d) * 2560 + 2048 + wt * 4, e[4], rb + OFF_BAR + B_T);
        }
      }
      mbar_wait(bar + B_T, s & 1);
      float p[10];
#pragma unroll
      for (int i = 0; i < 5; i++) { p[2 * i] = __uint_as_float(e[i] << 16); p[2 * i + 1] = __uint_as_float(e[i] & 0xffff0000u); }
#pragma unroll
      for (int d = 0; d < 2; d++) {
        const uint4 x = lds4u(sb + OFF_RT + d * 2560 + wt * 16);
        const uint32_t y = __float_as_uint(lds1f(sb + OFF_RT + d * 2560 + 2048 + wt * 4));
        p[0] += __uint_as_float(x.x << 16); p[1] += __uint_as_float(x.x & 0xffff0000u);
        p[2] += __uint_as_float(x.y << 16); p[3] += __uint_as_float(x.y & 0xffff0000u);
        p[4] += __uint_as_float(x.z << 16); p[5] += __uint_as_float(x.z & 0xffff0000u);
        p[6] += __uint_as_float(x.w << 16); p[7] += __uint_as_float(x.w & 0xffff0000u);
        p[8] += __uint_as_float(y << 16); p[9] += __uint_as_float(y & 0xffff0000u);
      }
      if (wt == 0) mbar_expect(bar + B_T, 2 * 2560);
      MemLoad<4> ml;
#pragma unroll
      for (int q = 0; q < 4; q++) ml.c[q] = make_float4(0.f, 0.f, 0.f, 0.f);
      if (!last) memload_issue(ml, s, warp, lane);
      {
        const int tq = 8 * w4 + (lane >> 2) - 2 * (lane & 3);
        float mx = fmaxf(p[8], p[9]);
#pragma unroll
        for (int i = 0; i < 8; i++) { if (8 * (i >> 1) + (i & 1) > tq) p[i] = -INFINITY; mx = fmaxf(mx, p[i]); }
        mx = fmaxf(mx, __shfl_xor_sync(~0u, mx, 1)); mx = fmaxf(mx, __shfl_xor_sync(~0u, mx, 2));
        float sum = 0.f;
#pragma unroll
        for (int i = 0; i < 10; i++) { p[i] = ex2(fmaf(p[i], sc, -mx * sc)); sum += p[i]; }
        sum += __shfl_xor_sync(~0u, sum, 1); sum += __shfl_xor_sync(~0u, sum, 2);
        const float inv = rcp(sum);
        const uint32_t pr = sb + OFF_P + (lane >> 3) * 800 + w4 * 32 + (lane & 7) * 4;
#pragma unroll
        for (int i = 0; i < 5; i++) sts1u(pr + i * 128, pack2(p[2 * i] * inv, p[2 * i + 1] * inv));
        sts1u(pr + 640, 0u);
      }
      if (!last) {
        memload_finish(ml, s, warp, lane, sb, (float)NCL);
        bar_arrive(NB_M, 384);
      }
      fence_async();
      bar_sync(NB_P, 128);
      {
        float o[16];
        uint64_t db = mkdesc(sb + OFF_P, 128, 800, 0);
        OPAQUE64(db);
        uint32_t vb[10];
#pragma unroll
        for (int i = 0; i < 10; i++) asm volatile("add.u32 %0, %1, %2;" : "=r"(vb[i]) : "r"(va[i]), "r"(zero));
        WG_FENCE();
        wg_rs32<0>(o, vb[0], vb[1], vb[2], vb[3], db);
        wg_rs32<1>(o, vb[4], vb[5], vb[6], vb[7], db + 16);
        wg_rs32<1>(o, vb[8], vb[9], 0u, 0u, db + 32);
        WG_COMMIT();
        uint4* dst = reinterpret_cast<uint4*>(g_oT) + ((s * HD + blockIdx.x * 64 + w4 * 16) * 4 + lane);
        WG_WAIT(0);
        dst[0] = make_uint4(pack2(o[0], o[1]), pack2(o[4], o[5]), pack2(o[8], o[9]), pack2(o[12], o[13]));
        dst[32] = make_uint4(pack2(o[2], o[3]), pack2(o[6], o[7]), pack2(o[10], o[11]), pack2(o[14], o[15]));
      }
    }
    bar_sync(NB_P, 128);
    if (tid0 == 256) { __threadfence(); atomicAdd(&g_flag[15], 1u); }
    cluster_sync();
  }
}

namespace hk {
constexpr int STAGES = 4, STAGE = 49152, OFF_ST = STAGES * STAGE, OFF_BAR = OFF_ST + 32768, SMEM = OFF_BAR + 1024, NCTA = NHELP;
constexpr int N_G1 = 192, SB0 = 12  , N_FULL = 5 * SB0, N_ITEMS = N_G1 + 20 + N_FULL + 5 * (2 + 4 + 7) + 1 + 35;
struct Item { int type, mb, nt, k0, k1, nsplit; };
__device__ __forceinline__ Item get_item(int i) {
  Item t;
  if (i < N_G1) { t.type = 0; t.mb = i / 12; t.nt = i % 12; t.k0 = 0; t.k1 = 10; t.nsplit = 1; return t; }
  i -= N_G1; t.type = 1; t.nt = i % 5;
  if (i < 20) { t.mb = SB0 + i / 5; t.k0 = 0; t.k1 = 24; t.nsplit = t.mb == 12 ? 3 : t.mb == 13 ? 5 : 8; return t; }
  i -= 20;
  if (i < N_FULL) { t.mb = i / 5; t.k0 = 0; t.k1 = 120; t.nsplit = 1; return t; }
  i -= N_FULL;
  int ns;
  if (i < 10) { t.mb = 12; ns = 2; } else if (i < 30) { i -= 10; t.mb = 13; ns = 4; } else if (i < 65) { i -= 30; t.mb = 14; ns = 7; }
  else if (i == 65) { t.type = 2; t.mb = t.k0 = t.k1 = 0; t.nsplit = 1; return t; }
  else { i -= 66; t.mb = 15; ns = 7; }
  t.nt = i % 5;
  const int p = i / 5;
  t.k0 = 24 + (96 * p) / ns; t.k1 = 24 + (96 * (p + 1)) / ns; t.nsplit = ns + 1;
  return t;
}
__device__ __forceinline__ void store_tile(const uint32_t* p, uint32_t stg, const CUtensorMap* tm, int c0, int r0, int wg, int t128) {
  const int lane = t128 & 31, r = (t128 >> 5) * 16 + (lane & 15);
  if (t128 == 0) asm volatile("cp.async.bulk.wait_group.read 0;" ::: "memory");
  bar_sync(1 + wg, 128);
#pragma unroll
  for (int j = 0; j < 8; j++) {
    const int c = 2 * j + (lane >> 4);
    const uint32_t a = stg + (c >> 3) * 8192 + r * 128 + (((c & 7) ^ (r & 7)) << 4);
    asm volatile("stmatrix.sync.aligned.m8n8.x4.shared.b16 [%0], {%1,%2,%3,%4};" :: "r"(a), "r"(p[4 * j]), "r"(p[4 * j + 1]), "r"(p[4 * j + 2]), "r"(p[4 * j + 3]) : "memory");
  }
  fence_async();
  bar_sync(1 + wg, 128);
  if (t128 == 0) {
    asm volatile("cp.async.bulk.tensor.2d.global.shared::cta.bulk_group [%0, {%2, %3}], [%1];" :: "l"(tm), "r"(stg), "r"(c0), "r"(r0) : "memory");
    asm volatile("cp.async.bulk.tensor.2d.global.shared::cta.bulk_group [%0, {%2, %3}], [%1];" :: "l"(tm), "r"(stg + 8192), "r"(c0 + 64), "r"(r0) : "memory");
    asm volatile("cp.async.bulk.commit_group;" ::: "memory");
  }
}
}
__global__ void __launch_bounds__(384, 1)
helper_kernel(const __grid_constant__ CUtensorMap tm_x, const __grid_constant__ CUtensorMap tm_g, const __grid_constant__ CUtensorMap tm_u,
              const __grid_constant__ CUtensorMap tm_h, const __grid_constant__ CUtensorMap tm_o, const __grid_constant__ CUtensorMap tm_wd,
              const __grid_constant__ CUtensorMap tm_wo, const __grid_constant__ CUtensorMap tm_hs, const __grid_constant__ CUtensorMap tm_out,
              const bf16* __restrict__ x) {
  using namespace hk;
  extern __shared__ __align__(1024) unsigned char smem[];
  const uint32_t sb = smem_u32(smem), bar = sb + OFF_BAR;
  const int tid = threadIdx.x, lane = tid & 31, wg = __shfl_sync(~0u, tid >> 7, 0);
  if (tid == 0) { for (int i = 0; i < STAGES; i++) { mbar_init(bar + 8 * i, 1); mbar_init(bar + 64 + 8 * i, 2); } asm volatile("fence.mbarrier_init.release.cluster;" ::: "memory"); }
  __syncthreads();
  const int i0 = blockIdx.x;
  if (wg == 2) {
    asm volatile("setmaxnreg.dec.sync.aligned.u32 40;");
    if (tid == 256) {
      uint32_t it = 0;
      wait_flag(&g_flag[F_LN], 96);
      wait_flag(&g_flag[F_W], 48);
      for (int i = i0; i < N_ITEMS; i += NCTA) {
        const Item t = get_item(i);
        const int m0 = t.mb * 128, n0 = t.nt * 128;
        int kb = t.k0;
        if (t.type == 1 && kb == 0) wait_flag(&g_flag[16 + t.mb], 24);
        for (; kb < t.k1 && kb < 24; kb++, it++) {
          const uint32_t st = it % STAGES, base = sb + st * STAGE, full = bar + 8 * st;
          mbar_wait_long(bar + 64 + 8 * st, ((it / STAGES) & 1) ^ 1);
          if (t.type == 0) {
            mbar_expect(full, 49152);
            tma2d(base, &tm_x, kb * 64, m0, full);
            tma2d(base + 16384, &tm_g, n0, kb * 64, full);
            tma2d(base + 24576, &tm_g, n0 + 64, kb * 64, full);
            tma2d(base + 32768, &tm_u, n0, kb * 64, full);
            tma2d(base + 40960, &tm_u, n0 + 64, kb * 64, full);
          } else {
            mbar_expect(full, 32768);
            tma2d(base, &tm_h, kb * 64, m0, full);
            tma2d(base + 16384, &tm_wd, n0, kb * 64, full);
            tma2d(base + 24576, &tm_wd, n0 + 64, kb * 64, full);
          }
        }
        const int kf = kb;
        for (; kb < t.k1; kb++, it++) {
          const uint32_t st = it % STAGES, base = sb + st * STAGE, full = bar + 8 * st;
          const int k0 = (kb - 24) * 64;
          mbar_wait_long(bar + 64 + 8 * st, ((it / STAGES) & 1) ^ 1);
          mbar_expect(full, 32768);
          tma2d(base + 16384, &tm_wo, n0, k0, full);
          tma2d(base + 24576, &tm_wo, n0 + 64, k0, full);
          if (kb == kf + STAGES - 2) {
            wait_flag(&g_flag[t.mb], 96);
            for (int j = STAGES - 2; j > 0; j--) tma3d(sb + ((it - j) % STAGES) * STAGE, &tm_o, 0, k0 - j * 64, m0 / 32, bar + 8 * ((it - j) % STAGES));
          }
          if (kb >= kf + STAGES - 2) tma3d(base, &tm_o, 0, k0, m0 / 32, full);
        }
      }
    }
  } else {
    asm volatile("setmaxnreg.inc.sync.aligned.u32 232;");
    uint32_t it = 0;
    for (int i = i0; i < N_ITEMS; i += NCTA) {
      const Item t = get_item(i);
      const int row = t.mb * 128 + wg * 64 + ((tid >> 5) & 3) * 16 + (lane >> 2);
      if (t.type == 2) continue;
      if (t.type == 0) {
        float dg[64], du[64];
#pragma unroll
        for (int j = 0; j < 64; j++) { dg[j] = 0.f; du[j] = 0.f; }
        for (int kb = 0; kb < 10; kb++, it++) {
          const uint32_t st = it % STAGES, base = sb + st * STAGE;
          mbar_wait_long(bar + 8 * st, (it / STAGES) & 1);
          const uint64_t da = mkdesc(base + wg * 8192, 16, 1024, 1), db = mkdesc(base + 16384, 8192, 1024, 1);
          WG_FENCE();
#pragma unroll
          for (int k = 0; k < 4; k++) { wg_ss128<0>(dg, da + 2 * k, db + 128 * k); wg_ss128<0>(du, da + 2 * k, db + 1024 + 128 * k); }
          WG_COMMIT();
          WG_WAIT(1);
          if (kb > 0 && (tid & 127) == 0) mbar_arrive(bar + 64 + 8 * ((it - 1) % STAGES));
        }
        WG_WAIT(0);
        if ((tid & 127) == 0) mbar_arrive(bar + 64 + 8 * ((it - 1) % STAGES));
        uint32_t p[32];
#pragma unroll
        for (int j = 0; j < 32; j++) p[j] = pack2(bfr(dg[2 * j]) * bfr(du[2 * j]), bfr(dg[2 * j + 1]) * bfr(du[2 * j + 1]));
        store_tile(p, sb + OFF_ST + wg * 16384, &tm_hs, t.nt * 128, t.mb * 128 + wg * 64, wg, tid & 127);
        if ((tid & 127) == 0) {
          asm volatile("cp.async.bulk.wait_group 0;" ::: "memory");
          asm volatile("fence.proxy.async;" ::: "memory");
          __threadfence(); atomicAdd(&g_flag[16 + t.mb], 1u);
        }
      } else {
        float d[64];
#pragma unroll
        for (int j = 0; j < 64; j++) d[j] = 0.f;
        uint32_t xr[32];
        {
          const uint32_t* xi = reinterpret_cast<const uint32_t*>(x + (size_t)row * DM + t.nt * 128 + (lane & 3) * 2);
#pragma unroll
          for (int j = 0; j < 16; j++) { xr[2 * j] = __ldg(xi + j * 4); xr[2 * j + 1] = __ldg(xi + j * 4 + 4 * DM); }
        }
        int kb = t.k0;
        for (; kb < t.k1 && kb < 24; kb++, it++) {
          const uint32_t st = it % STAGES, base = sb + st * STAGE;
          mbar_wait_long(bar + 8 * st, (it / STAGES) & 1);
          const uint64_t da = mkdesc(base + wg * 8192, 16, 1024, 1), db = mkdesc(base + 16384, 8192, 1024, 1);
          WG_FENCE();
#pragma unroll
          for (int k = 0; k < 4; k++) wg_ss128<0>(d, da + 2 * k, db + 128 * k);
          WG_COMMIT();
          WG_WAIT(1);
          if (kb > t.k0 && (tid & 127) == 0) mbar_arrive(bar + 64 + 8 * ((it - 1) % STAGES));
        }
        WG_WAIT(0);
        for (; kb < t.k1; kb++, it++) {
          const uint32_t st = it % STAGES, base = sb + st * STAGE;
          mbar_wait_long(bar + 8 * st, (it / STAGES) & 1);
          const uint64_t da = mkdesc(base + wg * 8192, 4096, 512, 2), db = mkdesc(base + 16384, 8192, 1024, 1);
          WG_FENCE();
#pragma unroll
          for (int k = 0; k < 4; k++) wg_ss128<1>(d, da + 64 * k, db + 128 * k);
          WG_COMMIT();
          WG_WAIT(1);
          if (kb > t.k0 && (tid & 127) == 0) mbar_arrive(bar + 64 + 8 * ((it - 1) % STAGES));
        }
        WG_WAIT(0);
        if ((tid & 127) == 0) mbar_arrive(bar + 64 + 8 * ((it - 1) % STAGES));
        {
          const uint32_t m = t.k0 == 0 ? 0xffff0000u : 0u;
#pragma unroll
          for (int j = 0; j < 32; j++) { d[2 * j] += __uint_as_float((xr[j] << 16) & m); d[2 * j + 1] += __uint_as_float(xr[j] & m); }
        }
        bool fin = true;
        if (t.nsplit > 1) {
          const int ti = (t.mb - SB0) * 5 + t.nt;
          float4* pp = g_part + ti * 4096 + tid;
#pragma unroll
          for (int j = 0; j < 16; j++) red4(pp + j * 256, d[4 * j], d[4 * j + 1], d[4 * j + 2], d[4 * j + 3]);
          bar_sync(1 + wg, 128);
          volatile unsigned* sflag = reinterpret_cast<volatile unsigned*>(smem + OFF_BAR + 256 + wg * 4);
          if ((tid & 127) == 0) {
            __threadfence();
            const unsigned old = atomicAdd(&g_flag[32 + ti], wg ? 0x10000u : 1u);
            *sflag = ((wg ? old >> 16 : old & 0xffffu) == (unsigned)t.nsplit - 1);
            __threadfence();
          }
          bar_sync(1 + wg, 128);
          fin = __shfl_sync(~0u, *sflag, 0) != 0;
          if (fin) {
#pragma unroll
            for (int j = 0; j < 16; j++) {
              const float4 u = __ldcg(pp + j * 256);
              d[4 * j] = u.x; d[4 * j + 1] = u.y; d[4 * j + 2] = u.z; d[4 * j + 3] = u.w;
            }
          }
        }
        if (fin) {
          uint32_t p[32];
#pragma unroll
          for (int j = 0; j < 32; j++) p[j] = pack2(d[2 * j], d[2 * j + 1]);
          store_tile(p, sb + OFF_ST + wg * 16384, &tm_out, t.nt * 128, t.mb * 128 + wg * 64, wg, tid & 127);
        }
      }
    }
    bar_sync(3, 256);
    if (tid >= 32 && tid < 64) {
      asm volatile("griddepcontrol.wait;" ::: "memory");
      unsigned old = 0;
      if (lane == 0) old = atomicAdd(&g_flag[F_DONE], 1u);
      if (__shfl_sync(~0u, old, 0) == NCTA - 1) { g_flag[lane] = 0; g_flag[32 + lane] = 0; }
    }
    if ((tid & 127) == 0) asm volatile("cp.async.bulk.wait_group 0;" ::: "memory");
  }
}

__global__ void fb_ln(const bf16* __restrict__ x) {
  uint2 u[5];
  const int row = blockIdx.x * 8 + (threadIdx.x >> 5), lane = threadIdx.x & 31;
  for (int j = 0; j < 5; j++) u[j] = reinterpret_cast<const uint2*>(x + (size_t)row * DM)[j * 32 + lane];
  ln_row(u, row, lane);
}
__global__ void fb_gemm(const bf16* A0, const bf16* A1, int m_split, const bf16* B, bf16* C0, bf16* C1, int N, int K, int mode, const bf16* R0, const bf16* R1) {
  const int n = blockIdx.x * blockDim.x + threadIdx.x, m = blockIdx.y;
  const bf16* a = m < m_split ? A0 + (size_t)m * K : A1 + (size_t)(m - m_split) * K;
  bf16* c = (m < m_split ? C0 + (size_t)m * N : C1 + (size_t)(m - m_split) * N) + n;
  float acc = 0.f;
  for (int k = 0; k < K; k++) acc += __bfloat162float(a[k]) * __bfloat162float(B[(size_t)k * N + n]);
  if (mode == 1) acc = bfr(acc) * __bfloat162float(*c);
  if (mode == 2) acc += __bfloat162float(R0[(size_t)m * N + n]) + __bfloat162float(R1[(size_t)m * N + n]);
  *c = __float2bfloat16_rn(acc);
}
__global__ void fb_attn(const bf16* q, const bf16* k, const bf16* v, bf16* o) {
  const int h = blockIdx.x, r = blockIdx.y, t = threadIdx.x;
  __shared__ float p[40];
  if (t < 40) {
    float a = 0.f;
    for (int e = 0; e < 192; e++) a += __bfloat162float(q[r * HD + h * 192 + e]) * __bfloat162float(k[t * HD + h * 192 + e]);
    p[t] = (r < 8 || r >= t) ? a * 0.07216878364870322f : -INFINITY;
  }
  __syncthreads();
  float mx = p[0], sum = 0.f, a = 0.f;
  for (int i = 1; i < 40; i++) mx = fmaxf(mx, p[i]);
  for (int i = 0; i < 40; i++) sum += __expf(p[i] - mx);
  for (int i = 0; i < 40; i++) a += bfr(__expf(p[i] - mx) / sum) * __bfloat162float(v[i * HD + h * 192 + t]);
  o[r * HD + h * 192 + t] = __float2bfloat16_rn(a);
}

typedef CUresult (*EncodeFn)(CUtensorMap*, CUtensorMapDataType, cuuint32_t, void*, const cuuint64_t*, const cuuint64_t*, const cuuint32_t*,
                             const cuuint32_t*, CUtensorMapInterleave, CUtensorMapSwizzle, CUtensorMapL2promotion, CUtensorMapFloatOOBfill);
static void make_map(EncodeFn enc, CUtensorMap* m, const void* p, int rank, const cuuint64_t* dims, const cuuint64_t* strides,
                     const cuuint32_t* box, CUtensorMapSwizzle swz) {
  cuuint32_t es[3] = {1, 1, 1};
  enc(m, CU_TENSOR_MAP_DATA_TYPE_BFLOAT16, rank, const_cast<void*>(p), dims, strides, box, es, CU_TENSOR_MAP_INTERLEAVE_NONE, swz,
      CU_TENSOR_MAP_L2_PROMOTION_L2_128B, CU_TENSOR_MAP_FLOAT_OOB_FILL_NONE);
}
static void map2d(EncodeFn enc, CUtensorMap* m, const void* p, int cols, int rows, int bc, int br, CUtensorMapSwizzle swz) {
  cuuint64_t dims[2] = {(cuuint64_t)cols, (cuuint64_t)rows}, strides[1] = {(cuuint64_t)cols * 2};
  cuuint32_t box[2] = {(cuuint32_t)bc, (cuuint32_t)br};
  make_map(enc, m, p, 2, dims, strides, box, swz);
}

extern "C" void kernel_launch(void* const* d_in, const int* in_sizes, int n_in, void* d_out, int out_size) {
  const bf16* x = (const bf16*)d_in[0];
  const bf16* mem0 = (const bf16*)d_in[1];
  const bf16* Wq = (const bf16*)d_in[2];
  const bf16* Wk = (const bf16*)d_in[3];
  const bf16* Wv = (const bf16*)d_in[4];
  const bf16* Wo = (const bf16*)d_in[5];
  const bf16* Wg = (const bf16*)d_in[8];
  const bf16* Wu = (const bf16*)d_in[9];
  const bf16* Wd = (const bf16*)d_in[10];
  bf16* out = (bf16*)d_out;

  void* fn = nullptr; cudaDriverEntryPointQueryResult qr;
  cudaGetDriverEntryPoint("cuTensorMapEncodeTiled", &fn, cudaEnableDefault, &qr);
  EncodeFn enc = (EncodeFn)fn;
  void *p_xn, *p_oT, *p_h;
  cudaGetSymbolAddress(&p_xn, g_xn); cudaGetSymbolAddress(&p_oT, g_oT); cudaGetSymbolAddress(&p_h, g_h);

  CUtensorMap t_x32, t_wv, t_wo16, t_x128, t_wg, t_wu, t_h, t_o, t_wd, t_wo64, t_hs, t_out, t_wq, t_wk;
  map2d(enc, &t_wq, Wq, HD, DM, 64, 128, CU_TENSOR_MAP_SWIZZLE_128B);
  map2d(enc, &t_wk, Wk, HD, DM, 64, 128, CU_TENSOR_MAP_SWIZZLE_128B);
  map2d(enc, &t_hs, p_h, FF, SEQ, 64, 64, CU_TENSOR_MAP_SWIZZLE_128B);
  map2d(enc, &t_out, out, DM, SEQ, 64, 64, CU_TENSOR_MAP_SWIZZLE_128B);
  map2d(enc, &t_x32, p_xn, DM, SEQ, 64, 32, CU_TENSOR_MAP_SWIZZLE_128B);
  map2d(enc, &t_wv, Wv, HD, DM, 64, 128, CU_TENSOR_MAP_SWIZZLE_128B);
  map2d(enc, &t_wo16, Wo, DM, HD, 16, 64, CU_TENSOR_MAP_SWIZZLE_32B);
  map2d(enc, &t_x128, p_xn, DM, SEQ, 64, 128, CU_TENSOR_MAP_SWIZZLE_128B);
  map2d(enc, &t_wg, Wg, FF, DM, 64, 64, CU_TENSOR_MAP_SWIZZLE_128B);
  map2d(enc, &t_wu, Wu, FF, DM, 64, 64, CU_TENSOR_MAP_SWIZZLE_128B);
  map2d(enc, &t_h, p_h, FF, SEQ, 64, 128, CU_TENSOR_MAP_SWIZZLE_128B);
  map2d(enc, &t_wd, Wd, DM, FF, 64, 64, CU_TENSOR_MAP_SWIZZLE_128B);
  map2d(enc, &t_wo64, Wo, DM, HD, 64, 64, CU_TENSOR_MAP_SWIZZLE_128B);
  {
    cuuint64_t dims[3] = {32, (cuuint64_t)HD, (cuuint64_t)NSEG}, strides[2] = {64, (cuuint64_t)HD * 64};
    cuuint32_t box[3] = {32, 64, 4};
    make_map(enc, &t_o, p_oT, 3, dims, strides, box, CU_TENSOR_MAP_SWIZZLE_64B);
  }
  cudaFuncSetAttribute(chain_kernel, cudaFuncAttributeMaxDynamicSharedMemorySize, ck::SMEM);
  cudaFuncSetAttribute(helper_kernel, cudaFuncAttributeMaxDynamicSharedMemorySize, hk::SMEM);

  cudaStream_t st = cudaStreamPerThread;
  {
    cudaLaunchConfig_t cfg = {};
    cfg.gridDim = dim3(ck::CL * ck::NCL); cfg.blockDim = dim3(384); cfg.dynamicSmemBytes = ck::SMEM; cfg.stream = st;
    cudaLaunchAttribute at[1];
    at[0].id = cudaLaunchAttributeClusterDimension; at[0].val.clusterDim.x = ck::CL; at[0].val.clusterDim.y = 1; at[0].val.clusterDim.z = 1;
    cfg.attrs = at; cfg.numAttrs = 1;
    int ncl = 0;
    if (cudaOccupancyMaxActiveClusters(&ncl, chain_kernel, &cfg) != cudaSuccess) { (void)cudaGetLastError(); ncl = 0; }
    if (ncl < ck::NCL) {
      bf16 *xn = (bf16*)p_xn, *h = (bf16*)p_h, *q = (bf16*)p_oT, *k = q + 40 * HD, *v = k + 40 * HD, *o = v + 40 * HD, *mem = o + 40 * HD, *att = mem + 8 * DM;
      fb_ln<<<SEQ / 8, 256, 0, st>>>(x);
      for (int s = 0; s < NSEG; s++) {
        const bf16 *m = s ? mem : mem0, *xs = xn + s * 32 * DM;
        fb_gemm<<<dim3(HD / 128, 40), 128, 0, st>>>(m, xs, 8, Wq, q, q + 8 * HD, HD, DM, 0, nullptr, nullptr);
        fb_gemm<<<dim3(HD / 128, 40), 128, 0, st>>>(m, xs, 8, Wk, k, k + 8 * HD, HD, DM, 0, nullptr, nullptr);
        fb_gemm<<<dim3(HD / 128, 40), 128, 0, st>>>(m, xs, 8, Wv, v, v + 8 * HD, HD, DM, 0, nullptr, nullptr);
        fb_attn<<<dim3(32, 40), 192, 0, st>>>(q, k, v, o);
        fb_gemm<<<dim3(DM / 128, 40), 128, 0, st>>>(o, o + 8 * HD, 8, Wo, mem, att + s * 32 * DM, DM, HD, 0, nullptr, nullptr);
      }
      fb_gemm<<<dim3(FF / 128, SEQ), 128, 0, st>>>(xn, xn, SEQ, Wg, h, h, FF, DM, 0, nullptr, nullptr);
      fb_gemm<<<dim3(FF / 128, SEQ), 128, 0, st>>>(xn, xn, SEQ, Wu, h, h, FF, DM, 1, nullptr, nullptr);
      fb_gemm<<<dim3(DM / 128, SEQ), 128, 0, st>>>(h, h, SEQ, Wd, out, out, DM, FF, 2, x, att);
      return;
    }
    cudaLaunchKernelEx(&cfg, chain_kernel, t_x32, t_wv, t_wo16, t_wq, t_wk, mem0, x, 0u);
  }
  {
    cudaLaunchConfig_t cfg = {};
    cfg.gridDim = dim3(hk::NCTA); cfg.blockDim = dim3(384); cfg.dynamicSmemBytes = hk::SMEM; cfg.stream = st;
    cudaLaunchAttribute at[1];
    at[0].id = cudaLaunchAttributeProgrammaticStreamSerialization; at[0].val.programmaticStreamSerializationAllowed = 1;
    cfg.attrs = at; cfg.numAttrs = 1;
    cudaLaunchKernelEx(&cfg, helper_kernel, t_x128, t_wg, t_wu, t_h, t_o, t_wd, t_wo64, t_hs, t_out, x);
  }
}
```

```cpp
#include <cuda_runtime.h>
#include <cuda_bf16.h>
#include <cuda.h>
#include <stdint.h>

typedef __nv_bfloat16 bf16;

constexpr int SEQ = 2048, DM = 640, HD = 6144, FF = 1536, NSEG = 64;
constexpr int ACC_CHUNKS = 1920;

__device__ __align__(1024) bf16 g_xn[SEQ * DM];
__device__ __align__(1024) bf16 g_oT[NSEG * HD * 32];
__device__ __align__(1024) bf16 g_h[SEQ * FF];
__device__ __align__(1024) float4 g_acc[NSEG * ACC_CHUNKS];
__device__ __align__(1024) float4 g_part[20 * 4096];
__device__ unsigned g_flag[64];

__device__ __forceinline__ uint32_t smem_u32(const void* p) { return (uint32_t)__cvta_generic_to_shared(p); }
__device__ __forceinline__ uint32_t mapa(uint32_t a, uint32_t r) { uint32_t o; asm("mapa.shared::cluster.u32 %0, %1, %2;" : "=r"(o) : "r"(a), "r"(r)); return o; }
__device__ __forceinline__ void mbar_init(uint32_t b, int c) { asm volatile("mbarrier.init.shared::cta.b64 [%0], %1;" :: "r"(b), "r"(c) : "memory"); }
__device__ __forceinline__ void mbar_expect(uint32_t b, uint32_t bytes) { asm volatile("mbarrier.arrive.expect_tx.shared::cta.b64 _, [%0], %1;" :: "r"(b), "r"(bytes) : "memory"); }
__device__ __forceinline__ void mbar_arrive(uint32_t b) { asm volatile("mbarrier.arrive.shared::cta.b64 _, [%0];" :: "r"(b) : "memory"); }
constexpr int SPIN_LIMIT = 1 << 20;
__device__ __forceinline__ void mbar_wait(uint32_t b, uint32_t ph) {
  asm volatile("{\n.reg .pred p;\n.reg .u32 n;\nmov.u32 n, 0;\n"
               "W: mbarrier.try_wait.parity.shared::cta.b64 p, [%0], %1;\n@p bra D;\n"
               "add.u32 n, n, 1;\nsetp.lt.u32 p, n, 0x40000;\n@p bra W;\ntrap;\nD:\n}" :: "r"(b), "r"(ph) : "memory");
}
__device__ __forceinline__ void mbar_wait_long(uint32_t b, uint32_t ph) {
  asm volatile("{\n.reg .pred p;\n.reg .u32 n;\nmov.u32 n, 0;\n"
               "W: mbarrier.try_wait.parity.shared::cta.b64 p, [%0], %1;\n@p bra D;\n"
               "add.u32 n, n, 1;\nsetp.lt.u32 p, n, 0x400000;\n@p bra W;\ntrap;\nD:\n}" :: "r"(b), "r"(ph) : "memory");
}
__device__ __forceinline__ void bar_sync(int id, int n) { asm volatile("bar.sync %0, %1;" :: "r"(id), "r"(n) : "memory"); }
__device__ __forceinline__ void bar_arrive(int id, int n) { asm volatile("bar.arrive %0, %1;" :: "r"(id), "r"(n) : "memory"); }
__device__ __forceinline__ void fence_async() { asm volatile("fence.proxy.async.shared::cta;" ::: "memory"); }
__device__ __forceinline__ void cluster_sync() { asm volatile("barrier.cluster.arrive.release.aligned;\nbarrier.cluster.wait.acquire.aligned;" ::: "memory"); }
__device__ __forceinline__ void tma2d(uint32_t dst, const CUtensorMap* m, int c0, int c1, uint32_t bar) {
  asm volatile("cp.async.bulk.tensor.2d.shared::cluster.global.mbarrier::complete_tx::bytes [%0], [%1, {%3, %4}], [%2];"
               :: "r"(dst), "l"(m), "r"(bar), "r"(c0), "r"(c1) : "memory");
}
__device__ __forceinline__ void tma2d_mc(uint32_t dst, const CUtensorMap* m, int c0, int c1, uint32_t bar, uint16_t mask) {
  asm volatile("cp.async.bulk.tensor.2d.shared::cluster.global.mbarrier::complete_tx::bytes.multicast::cluster [%0], [%1, {%3, %4}], [%2], %5;"
               :: "r"(dst), "l"(m), "r"(bar), "r"(c0), "r"(c1), "h"(mask) : "memory");
}
__device__ __forceinline__ void tma3d(uint32_t dst, const CUtensorMap* m, int c0, int c1, int c2, uint32_t bar) {
  asm volatile("cp.async.bulk.tensor.3d.shared::cluster.global.mbarrier::complete_tx::bytes [%0], [%1, {%3, %4, %5}], [%2];"
               :: "r"(dst), "l"(m), "r"(bar), "r"(c0), "r"(c1), "r"(c2) : "memory");
}
__device__ __forceinline__ void st_async1(uint32_t a, uint32_t x, uint32_t mb) {
  asm volatile("st.async.weak.shared::cluster.mbarrier::complete_tx::bytes.b32 [%0], %1, [%2];" :: "r"(a), "r"(x), "r"(mb) : "memory");
}
__device__ __forceinline__ void st_async2(uint32_t a, uint32_t x, uint32_t y, uint32_t mb) {
  asm volatile("st.async.weak.shared::cluster.mbarrier::complete_tx::bytes.v2.b32 [%0], {%1,%2}, [%3];" :: "r"(a), "r"(x), "r"(y), "r"(mb) : "memory");
}
__device__ __forceinline__ void st_async4(uint32_t a, uint32_t x, uint32_t y, uint32_t z, uint32_t w, uint32_t mb) {
  asm volatile("st.async.weak.shared::cluster.mbarrier::complete_tx::bytes.v4.b32 [%0], {%1,%2,%3,%4}, [%5];" :: "r"(a), "r"(x), "r"(y), "r"(z), "r"(w), "r"(mb) : "memory");
}
__device__ __forceinline__ void ldsm4(uint32_t& r0, uint32_t& r1, uint32_t& r2, uint32_t& r3, uint32_t a) {
  asm volatile("ldmatrix.sync.aligned.m8n8.x4.shared.b16 {%0,%1,%2,%3}, [%4];" : "=r"(r0), "=r"(r1), "=r"(r2), "=r"(r3) : "r"(a) : "memory");
}
__device__ __forceinline__ void ldsm4t(uint32_t& r0, uint32_t& r1, uint32_t& r2, uint32_t& r3, uint32_t a) {
  asm volatile("ldmatrix.sync.aligned.m8n8.x4.trans.shared.b16 {%0,%1,%2,%3}, [%4];" : "=r"(r0), "=r"(r1), "=r"(r2), "=r"(r3) : "r"(a) : "memory");
}
__device__ __forceinline__ void stsm4t(uint32_t a, uint32_t r0, uint32_t r1, uint32_t r2, uint32_t r3) {
  asm volatile("stmatrix.sync.aligned.m8n8.x4.trans.shared.b16 [%0], {%1,%2,%3,%4};" :: "r"(a), "r"(r0), "r"(r1), "r"(r2), "r"(r3) : "memory");
}
__device__ __forceinline__ void stsm1t(uint32_t a, uint32_t r0) {
  asm volatile("stmatrix.sync.aligned.m8n8.x1.trans.shared.b16 [%0], {%1};" :: "r"(a), "r"(r0) : "memory");
}
__device__ __forceinline__ void stsm2t(uint32_t a, uint32_t r0, uint32_t r1) {
  asm volatile("stmatrix.sync.aligned.m8n8.x2.trans.shared.b16 [%0], {%1,%2};" :: "r"(a), "r"(r0), "r"(r1) : "memory");
}
__device__ __forceinline__ void mma16816(float* d, uint32_t a0, uint32_t a1, uint32_t a2, uint32_t a3, uint32_t b0, uint32_t b1) {
  asm volatile("mma.sync.aligned.m16n8k16.row.col.f32.bf16.bf16.f32 {%0,%1,%2,%3}, {%4,%5,%6,%7}, {%8,%9}, {%0,%1,%2,%3};"
               : "+f"(d[0]), "+f"(d[1]), "+f"(d[2]), "+f"(d[3]) : "r"(a0), "r"(a1), "r"(a2), "r"(a3), "r"(b0), "r"(b1));
}
__device__ __forceinline__ void mma1688(float* d, uint32_t a0, uint32_t a1, uint32_t b0) {
  asm volatile("mma.sync.aligned.m16n8k8.row.col.f32.bf16.bf16.f32 {%0,%1,%2,%3}, {%4,%5}, {%6}, {%0,%1,%2,%3};"
               : "+f"(d[0]), "+f"(d[1]), "+f"(d[2]), "+f"(d[3]) : "r"(a0), "r"(a1), "r"(b0));
}
__device__ __forceinline__ float ex2(float x) { float r; asm("ex2.approx.ftz.f32 %0, %1;" : "=f"(r) : "f"(x)); return r; }
__device__ __forceinline__ float rcp(float x) { float r; asm("rcp.approx.ftz.f32 %0, %1;" : "=f"(r) : "f"(x)); return r; }
__device__ __forceinline__ uint32_t pack2(float lo, float hi) { uint32_t r; asm("cvt.rn.bf16x2.f32 %0, %1, %2;" : "=r"(r) : "f"(hi), "f"(lo)); return r; }
__device__ __forceinline__ float2 lds2f(uint32_t a) { float2 v; asm volatile("ld.shared.v2.f32 {%0,%1}, [%2];" : "=f"(v.x), "=f"(v.y) : "r"(a) : "memory"); return v; }
__device__ __forceinline__ float4 lds4f(uint32_t a) { float4 v; asm volatile("ld.shared.v4.f32 {%0,%1,%2,%3}, [%4];" : "=f"(v.x), "=f"(v.y), "=f"(v.z), "=f"(v.w) : "r"(a) : "memory"); return v; }
__device__ __forceinline__ uint4 lds4u(uint32_t a) { uint4 v; asm volatile("ld.shared.v4.u32 {%0,%1,%2,%3}, [%4];" : "=r"(v.x), "=r"(v.y), "=r"(v.z), "=r"(v.w) : "r"(a) : "memory"); return v; }
__device__ __forceinline__ float lds1f(uint32_t a) { float v; asm volatile("ld.shared.f32 %0, [%1];" : "=f"(v) : "r"(a) : "memory"); return v; }
__device__ __forceinline__ void sts4f(uint32_t a, float x, float y, float z, float w) { asm volatile("st.shared.v4.f32 [%0], {%1,%2,%3,%4};" :: "r"(a), "f"(x), "f"(y), "f"(z), "f"(w) : "memory"); }
__device__ __forceinline__ void sts2f(uint32_t a, float x, float y) { asm volatile("st.shared.v2.f32 [%0], {%1,%2};" :: "r"(a), "f"(x), "f"(y) : "memory"); }
__device__ __forceinline__ void sts1f(uint32_t a, float x) { asm volatile("st.shared.f32 [%0], %1;" :: "r"(a), "f"(x) : "memory"); }
__device__ __forceinline__ void sts1u(uint32_t a, uint32_t x) { asm volatile("st.shared.u32 [%0], %1;" :: "r"(a), "r"(x) : "memory"); }
__device__ __forceinline__ void sts4u(uint32_t a, uint4 v) { asm volatile("st.shared.v4.u32 [%0], {%1,%2,%3,%4};" :: "r"(a), "r"(v.x), "r"(v.y), "r"(v.z), "r"(v.w) : "memory"); }
__device__ __forceinline__ float4 ld_relaxed4(const float4* p) {
  float4 r; asm volatile("ld.relaxed.gpu.global.v4.f32 {%0,%1,%2,%3}, [%4];" : "=f"(r.x), "=f"(r.y), "=f"(r.z), "=f"(r.w) : "l"(p) : "memory"); return r;
}
__device__ __forceinline__ void red4(float4* p, float a, float b, float c, float d) {
  asm volatile("red.relaxed.gpu.global.add.v4.f32 [%0], {%1,%2,%3,%4};" :: "l"(p), "f"(a), "f"(b), "f"(c), "f"(d) : "memory");
}
__device__ __forceinline__ uint64_t mkdesc(uint32_t addr, uint32_t lbo, uint32_t sbo, uint32_t swz) {
  return (uint64_t)((addr & 0x3FFFF) >> 4) | ((uint64_t)(lbo >> 4) << 16) | ((uint64_t)(sbo >> 4) << 32) | ((uint64_t)swz << 62);
}
#define WG_FENCE() asm volatile("wgmma.fence.sync.aligned;" ::: "memory")
#define WG_COMMIT() asm volatile("wgmma.commit_group.sync.aligned;" ::: "memory")
#define WG_WAIT(n) asm volatile("wgmma.wait_group.sync.aligned %0;" :: "n"(n) : "memory")
#define OPAQUE64(x) asm volatile("" : "+l"(x))

#define F4(d, i) "+f"(d[i]), "+f"(d[i + 1]), "+f"(d[i + 2]), "+f"(d[i + 3])
#define F16(d, i) F4(d, i), F4(d, i + 4), F4(d, i + 8), F4(d, i + 12)
template <int ACC>
__device__ __forceinline__ void wg_rs32(float* d, uint32_t a0, uint32_t a1, uint32_t a2, uint32_t a3, uint64_t b) {
  asm volatile("wgmma.mma_async.sync.aligned.m64n32k16.f32.bf16.bf16 {%0,%1,%2,%3,%4,%5,%6,%7,%8,%9,%10,%11,%12,%13,%14,%15}, {%16,%17,%18,%19}, %20, %21, 1, 1, 0;"
               : F16(d, 0) : "r"(a0), "r"(a1), "r"(a2), "r"(a3), "l"(b), "n"(ACC));
}
template <int ACC>
__device__ __forceinline__ void wg_rs32x(float* d, uint32_t a0, uint32_t a1, uint32_t a2, uint32_t a3, uint32_t blo) {
  asm volatile("{\n.reg .b64 b;\nmov.b64 b, {%20, 0x40000040};\n"
               "wgmma.mma_async.sync.aligned.m64n32k16.f32.bf16.bf16 {%0,%1,%2,%3,%4,%5,%6,%7,%8,%9,%10,%11,%12,%13,%14,%15}, {%16,%17,%18,%19}, b, %21, 1, 1, 0;\n}"
               : F16(d, 0) : "r"(a0), "r"(a1), "r"(a2), "r"(a3), "r"(blo), "n"(ACC));
}
template <int ACC>
__device__ __forceinline__ void wg_rs40(float* d, uint32_t a0, uint32_t a1, uint32_t a2, uint32_t a3, uint64_t b) {
  asm volatile("wgmma.mma_async.sync.aligned.m64n40k16.f32.bf16.bf16 {%0,%1,%2,%3,%4,%5,%6,%7,%8,%9,%10,%11,%12,%13,%14,%15,%16,%17,%18,%19}, {%20,%21,%22,%23}, %24, %25, 1, 1, 0;"
               : F16(d, 0), F4(d, 16) : "r"(a0), "r"(a1), "r"(a2), "r"(a3), "l"(b), "n"(ACC));
}
template <int ACC>
__device__ __forceinline__ void wg_ss8(float* d, uint64_t a, uint64_t b) {
  asm volatile("wgmma.mma_async.sync.aligned.m64n8k16.f32.bf16.bf16 {%0,%1,%2,%3}, %4, %5, %6, 1, 1, 0, 0;" : F4(d, 0) : "l"(a), "l"(b), "n"(ACC));
}
template <int ACC, int TA>
__device__ __forceinline__ void wg_ss40(float* d, uint64_t a, uint64_t b) {
  asm volatile("wgmma.mma_async.sync.aligned.m64n40k16.f32.bf16.bf16 {%0,%1,%2,%3,%4,%5,%6,%7,%8,%9,%10,%11,%12,%13,%14,%15,%16,%17,%18,%19}, %20, %21, %22, 1, 1, %23, 0;"
               : F16(d, 0), F4(d, 16) : "l"(a), "l"(b), "n"(ACC), "n"(TA));
}
template <int TA>
__device__ __forceinline__ void wg_ss128(float* d, uint64_t a, uint64_t b) {
  asm volatile("wgmma.mma_async.sync.aligned.m64n128k16.f32.bf16.bf16 {"
               "%0,%1,%2,%3,%4,%5,%6,%7,%8,%9,%10,%11,%12,%13,%14,%15,%16,%17,%18,%19,%20,%21,%22,%23,%24,%25,%26,%27,%28,%29,%30,%31,"
               "%32,%33,%34,%35,%36,%37,%38,%39,%40,%41,%42,%43,%44,%45,%46,%47,%48,%49,%50,%51,%52,%53,%54,%55,%56,%57,%58,%59,%60,%61,%62,%63"
               "}, %64, %65, 1, 1, 1, %66, 1;"
               : F16(d, 0), F16(d, 16), F16(d, 32), F16(d, 48) : "l"(a), "l"(b), "n"(TA));
}

__device__ __forceinline__ float bfr(float x) { return __bfloat162float(__float2bfloat16_rn(x)); }
constexpr int F_LN = 52, F_DONE = 53, F_W = 54, NHELP = 36;
__device__ __forceinline__ void ln_row(const uint2 (&u)[5], int row, int lane) {
  float v[20];
#pragma unroll
  for (int i = 0; i < 5; i++) {
    v[4 * i + 0] = __uint_as_float(u[i].x << 16); v[4 * i + 1] = __uint_as_float(u[i].x & 0xffff0000u);
    v[4 * i + 2] = __uint_as_float(u[i].y << 16); v[4 * i + 3] = __uint_as_float(u[i].y & 0xffff0000u);
  }
  float s = 0.f;
#pragma unroll
  for (int i = 0; i < 20; i++) s += v[i];
#pragma unroll
  for (int o = 16; o; o >>= 1) s += __shfl_xor_sync(~0u, s, o);
  const float mean = s * (1.0f / DM);
  float q = 0.f;
#pragma unroll
  for (int i = 0; i < 20; i++) { float d = v[i] - mean; q += d * d; }
#pragma unroll
  for (int o = 16; o; o >>= 1) q += __shfl_xor_sync(~0u, q, o);
  const float mb = bfr(mean), rs = 1.0f / bfr(sqrtf(bfr(bfr(q * (1.0f / DM)) + 1e-5f)));
  uint2* dst = reinterpret_cast<uint2*>(g_xn + (size_t)row * DM);
#pragma unroll
  for (int i = 0; i < 5; i++) {
    uint2 o;
    o.x = pack2(bfr(v[4 * i + 0] - mb) * rs, bfr(v[4 * i + 1] - mb) * rs);
    o.y = pack2(bfr(v[4 * i + 2] - mb) * rs, bfr(v[4 * i + 3] - mb) * rs);
    dst[i * 32 + lane] = o;
  }
}
__device__ __forceinline__ void wait_flag(const unsigned* f, unsigned target) {
  unsigned v; int n = 0;
  while (true) {
    asm volatile("ld.acquire.gpu.global.u32 %0, [%1];" : "=r"(v) : "l"(f) : "memory");
    if (v >= target) break;
    if (++n > (1 << 21)) __trap();
    __nanosleep(100);
  }
  asm volatile("fence.proxy.async.global;" ::: "memory");
}

namespace ck {
constexpr int CL = 6, NCL = 16, NRF = 8, NSS = 40 - NRF, NTP = 1;
constexpr uint32_t OFF_H = 0, OFF_WV = 51200, OFF_WO = OFF_WV + NSS * 2048, OFF_Q = OFF_WO + 86016, OFF_K = OFF_Q + 5120,
                   OFF_OG = OFF_K + 5120, OFF_RA = OFF_OG + 6144, OFF_P = OFF_RA + 3840, OFF_RT = OFF_P + 3200,
                   OFF_BAR = OFF_RT + 5120, SMEM = OFF_BAR + 256;
constexpr uint32_t B_X = 0, B_A = 8, B_T = 16, B_W = 24, B_WR = 32, B_B = 40  , B_XF = 88, B_DUMMY = 96, B_WO = 104,
                   B_ST = 128  ;
enum { NB_M = 1, NB_QK = 2, NB_PM = 3, NB_V = 4, NB_TS = 5, NB_P = 6, NB_G = 7, NB_R = 8  , NB_S = 12, NB_V2 = 13 };
static_assert(SMEM <= 232448, "smem");
static_assert(OFF_WO % 1024 == 0 && OFF_Q % 1024 == 0, "align");
}
__device__ __forceinline__ uint32_t opq(uint32_t x) { asm volatile("" : "+r"(x)); return x; }

__device__ __forceinline__ uint32_t memrow_addr(uint32_t sb, uint32_t col0, uint32_t m) {
  return sb + ck::OFF_H + (col0 >> 6) * 5120 + 4096 + m * 128 + ((((col0 >> 3) & 7) ^ m) << 4);
}
constexpr int VLEAD = 5;
constexpr int LW = 21;
constexpr int DEPTH = 2;
template <int N> struct MemLoad { float4 c[N]; };
template <int N>
__device__ __forceinline__ void memload_issue(MemLoad<N>& m, int s, uint32_t warp, uint32_t lane) {
  const float4* p = g_acc + (s * ACC_CHUNKS + warp * 160) + lane;
#pragma unroll
  for (int q = 0; q < N; q++) m.c[q] = ld_relaxed4(p + q * 32);
}
template <int N>
__device__ __forceinline__ void memload_finish(MemLoad<N>& m, int s, uint32_t warp, uint32_t lane0, uint32_t sb, float full) {
  const uint32_t lane = opq(lane0);
  const uint32_t a4 = memrow_addr(sb, warp * 48 + (lane >> 3) * 8, lane & 7), a2 = memrow_addr(sb, warp * 48 + 32 + ((lane >> 3) & 1) * 8, lane & 7);
  const uint32_t a1 = memrow_addr(sb, 576 + warp * 8, lane & 7);
  int n = 0;
  while (true) {
    bool ok = true;
#pragma unroll
    for (int q = 0; q < N; q++) ok = ok && m.c[q].w == full;
    if (__all_sync(~0u, ok)) break;
    if (++n > SPIN_LIMIT) __trap();
    memload_issue(m, s, warp, opq(lane0));
  }
  const float4* c = m.c;
  stsm4t(a4, pack2(c[0].x, c[1].x), pack2(c[2].x, c[3].x), pack2(c[0].y, c[1].y), pack2(c[2].y, c[3].y));
  stsm2t(a2, pack2(c[0].z, c[1].z), pack2(c[2].z, c[3].z));
  if (N == 5) stsm1t(a1, pack2(c[N - 1].x, c[N - 1].y + c[N - 1].z));
}
#define WO_PREFETCH() _Pragma("unroll") for (int i = 0; i < 6; i++) \
  ldsm4t(f[i / 3][4 * (i % 3)], f[i / 3][4 * (i % 3) + 1], f[i / 3][4 * (i % 3) + 2], f[i / 3][4 * (i % 3) + 3], wo + (i % 3) * 12288 + (i / 3) * 2048)
#define HOFF(k) ((uint64_t)((((k) >> 2) * 5120 + ((k) & 3) * 32) >> 4))

template <bool LOADS>
__device__ __forceinline__ void token_qk(const uint32_t* a, int s, uint32_t sb, uint32_t warp, uint32_t lane0, uint32_t zero) {
  using namespace ck;
  const uint32_t bar = sb + OFF_BAR;
  float d[16];
  MemLoad<5> ml;
  mbar_wait(bar + B_X, (s + 1) & 1);
  const uint32_t db = opq((uint32_t)mkdesc(sb + OFF_H, 16, 1024, 1));
  WG_FENCE();
  wg_rs32x<0>(d, a[0], a[1], a[2], a[3], db);
#pragma unroll
  for (int k = 1; k < 40; k++) {
    wg_rs32x<1>(d, a[4 * k], a[4 * k + 1], a[4 * k + 2], a[4 * k + 3], db + (uint32_t)HOFF(k));
    if (LOADS && k == LW) WG_COMMIT();
  }
  WG_COMMIT();
  if (LOADS) { WG_WAIT(1); do { memload_issue(ml, s, warp, opq(lane0)); } while (zero >> 31); }
  WG_WAIT(0);
  const uint32_t e0 = pack2(d[0], d[1]);
  const uint32_t lane = opq(lane0), wg = warp >> 2, w4 = warp & 3;
  const uint32_t mat = lane >> 3, i = lane & 7, h = mat & 1, j0 = mat >> 1;
  const uint32_t ep0 = sb + OFF_Q + wg * 5120 + (8 * j0 + i) * 128 + (((2 * w4 + h) ^ i) << 4), ep1 = ep0 + 2048;
  stsm4t(ep0, e0, pack2(d[2], d[3]), pack2(d[4], d[5]), pack2(d[6], d[7]));
  stsm4t(ep1, pack2(d[8], d[9]), pack2(d[10], d[11]), pack2(d[12], d[13]), pack2(d[14], d[15]));
  if (LOADS) memload_finish(ml, s, warp, lane, sb, __uint_as_float(__float_as_uint((float)NCL) + (e0 & zero)));
}

__global__ void __launch_bounds__(384, 1)
chain_kernel(const __grid_constant__ CUtensorMap tm_x, const __grid_constant__ CUtensorMap tm_wv, const __grid_constant__ CUtensorMap tm_wo,
             const __grid_constant__ CUtensorMap tm_wq, const __grid_constant__ CUtensorMap tm_wk, const bf16* __restrict__ mem0,
             const bf16* __restrict__ x, uint32_t zero) {
  using namespace ck;
  extern __shared__ __align__(1024) unsigned char smem[];
  const uint32_t sb = smem_u32(smem);
  const uint32_t tid0 = threadIdx.x;
  const uint32_t warp = __shfl_sync(~0u, threadIdx.x >> 5, 0);
  const int rank = blockIdx.x % CL, cluster = blockIdx.x / CL;
  const int hb = (rank / 3) * 3, j3 = rank % 3;
  const uint32_t bar = sb + OFF_BAR;

  asm volatile("griddepcontrol.launch_dependents;");
  const int gw = (tid0 >> 5) * 96 + blockIdx.x;
  uint2 xu[2][5];
  uint4 m0u[5];
#pragma unroll
  for (int r = 0; r < 5; r++) m0u[r] = __ldg(reinterpret_cast<const uint4*>(mem0) + (tid0 & 127) + r * 128);
#pragma unroll
  for (int r = 0; r < 2; r++) {
    const int row = min(gw + r * 1152, SEQ - 1);
#pragma unroll
    for (int j = 0; j < 5; j++) xu[r][j] = __ldg(reinterpret_cast<const uint2*>(x + (size_t)row * DM) + j * 32 + (tid0 & 31));
  }
  if (tid0 == 0) {
    mbar_init(bar + B_X, 1); mbar_init(bar + B_A, 1); mbar_init(bar + B_T, 1); mbar_init(bar + B_W, 1); mbar_init(bar + B_WR, 1);
    for (int i = 0; i < 3; i++) mbar_init(bar + B_B + 8 * i, 1);
    for (int i = 0; i < 10; i++) mbar_init(bar + B_ST + 8 * i, 1);
    mbar_init(bar + B_XF, 1); mbar_init(bar + B_WO, 1);
    asm volatile("fence.mbarrier_init.release.cluster;" ::: "memory");
    mbar_expect(bar + B_A, 3 * 1024); mbar_expect(bar + B_T, 2 * 2560);
    for (int i = 0; i < 3; i++) mbar_expect(bar + B_B + 8 * i, 2048);
    for (int i = 0; i < 10; i++) mbar_expect(bar + B_ST + 8 * i, 16384);
    mbar_expect(bar + B_XF, CL * 4);
    mbar_expect(bar + B_X, 40960);
    mbar_expect(bar + B_WR, NRF * 2048);
    mbar_expect(bar + B_W, NSS * 2048); mbar_expect(bar + B_WO, (rank < 4 ? 7 : 6) * 12288);
    tma2d(sb + OFF_H, &tm_wv, blockIdx.x * 64, NSS * 16, bar + B_WR);
  }
  {
    const float4 z = make_float4(0.f, 0.f, 0.f, 0.f);
    for (int j = blockIdx.x * 384 + tid0; j < NSEG * ACC_CHUNKS; j += 96 * 384) g_acc[j] = z;
    for (int j = blockIdx.x * 384 + tid0; j < 20 * 4096; j += 96 * 384) g_part[j] = z;
  }
#pragma unroll 1
  for (int r = 0; r < 2; r++) {
    if (gw + r * 1152 < SEQ) ln_row(xu[0], gw + r * 1152, tid0 & 31);
#pragma unroll
    for (int j = 0; j < 5; j++) xu[0][j] = xu[1][j];
    if (r == 0 && tid0 < 2 * DEPTH) {
      const uint32_t wg = tid0 & 1, i = tid0 >> 1;
      tma2d(sb + (wg == 0 ? OFF_WO + i * 16384 : i < 4 ? OFF_WV + i * 16384 : OFF_Q), wg == 0 ? &tm_wq : &tm_wk, blockIdx.x * 64, i * 128,
            bar + B_ST + 8 * (wg * 5 + i));
    }
    __syncwarp();
  }
  __threadfence();
  __syncthreads();
  if (tid0 == 320) atomicAdd(&g_flag[F_LN], 1u);

  if (warp < 8) {
    asm volatile("setmaxnreg.inc.sync.aligned.u32 208;");
    const uint32_t lane0 = __shfl_sync(~0u, opq(threadIdx.x & 31), threadIdx.x & 31);
    uint32_t a[160];
    {
      const uint32_t wg = warp >> 2, l7 = lane0 & 7, l3 = lane0 >> 3, t128 = tid0 & 127;
      const uint32_t lo = ((l3 >> 1) * 8 + l7) * 128 + (((2 * (warp & 3) + (l3 & 1)) ^ l7) << 4);
#pragma unroll
      for (int i = 0; i < 5; i++) {
        const uint32_t base = sb + (wg == 0 ? OFF_WO + i * 16384 : i < 4 ? OFF_WV + i * 16384 : OFF_Q) + lo;
        mbar_wait(bar + B_ST + 8 * (wg * 5 + i), 0);
        if (i + DEPTH < 5 && t128 == 0)
          tma2d(sb + (wg == 0 ? OFF_WO + (i + DEPTH) * 16384 : i + DEPTH < 4 ? OFF_WV + (i + DEPTH) * 16384 : OFF_Q), wg == 0 ? &tm_wq : &tm_wk,
                blockIdx.x * 64, (i + DEPTH) * 128, bar + B_ST + 8 * (wg * 5 + i + DEPTH));
        __syncwarp();
#pragma unroll
        for (int k = 0; k < 8; k++) ldsm4t(a[32 * i + 4 * k], a[32 * i + 4 * k + 1], a[32 * i + 4 * k + 2], a[32 * i + 4 * k + 3], base + k * 2048);
        asm volatile("" :: "r"(a[32 * i]), "r"(a[32 * i + 4]), "r"(a[32 * i + 8]), "r"(a[32 * i + 12]), "r"(a[32 * i + 16]), "r"(a[32 * i + 20]), "r"(a[32 * i + 24]), "r"(a[32 * i + 28]) : "memory");
        bar_sync(NB_R + wg, 128);
        if (wg == 1) {
          if (i >= 3 && t128 < 2) tma2d(sb + OFF_WV + ((i - 3) * 2 + t128) * 16384, &tm_wv, blockIdx.x * 64, ((i - 3) * 2 + t128) * 128, bar + B_W);
        } else if (i == 4) {
          const int t = t128 / 6, d = t128 % 6;
          if (t < (rank < 4 ? 7 : 6)) tma2d(sb + OFF_WO + t * 12288 + d * 2048, &tm_wo, t < 6 ? rank * 96 + t * 16 : 576 + rank * 16,
                                            cluster * 384 + ((rank + CL - d) % CL) * 64, bar + B_WO);
        }
        __syncwarp();
      }
      bar_sync(NB_QK, 256);
      asm volatile("barrier.cluster.arrive.relaxed.aligned;" ::: "memory");
    }
    token_qk<false>(a, -1, sb, warp, lane0, zero);
    asm volatile("barrier.cluster.wait.acquire.aligned;" ::: "memory");
    const float sc = 0.07216878364870322f * 1.4426950408889634f;

    for (int s = 0;; s++) {
      uint32_t lane;
      {
        const uint32_t ln = opq(lane0);
        const uint32_t x0 = sb + OFF_H + 4096 + (ln & 7) * 128 + (((ln >> 3) ^ (ln & 7)) << 4), x1 = x0 ^ 64;
        float c[16];
#pragma unroll
        for (int i = 0; i < 16; i++) c[i] = 0.f;
        uint32_t bf[1][16];
        bar_sync(NB_M, 384);
#pragma unroll
        for (int k = 0; k < 40; k += 2) {
          uint32_t* b = bf[0] + 12;
          ldsm4(b[0], b[1], b[2], b[3], ((k & 2) ? x1 : x0) + (k >> 2) * 5120);
          float* d = c + ((k & 2) ? 8 : 0);
          mma16816(d, a[4 * k], a[4 * k + 1], a[4 * k + 2], a[4 * k + 3], b[0], b[1]);
          mma16816(d + 4, a[4 * k + 4], a[4 * k + 5], a[4 * k + 6], a[4 * k + 7], b[2], b[3]);
        }
#pragma unroll
        for (int i = 0; i < 4; i++) c[i] = (c[i] + c[4 + i]) + (c[8 + i] + c[12 + i]);
        asm volatile("add.u32 %0, %1, %2;" : "=r"(lane) : "r"(lane0), "r"(bf[0][15] & zero));
        const uint32_t qst = sb + OFF_Q + (warp >> 2) * 5120 + (32 + (lane & 7)) * 128 + (((2 * (warp & 3) + ((lane >> 3) & 1)) ^ (lane & 7)) << 4);
        stsm2t(qst, pack2(c[0], c[1]), pack2(c[2], c[3]));
      }
      const uint32_t l7 = lane & 7, l3 = lane >> 3;
      fence_async();
      bar_arrive(NB_S, 384);
      if (s == NSEG - 1) break;
      if (s == 0) { mbar_wait(bar + B_WO, 0); if (tid0 == 64) atomicAdd(&g_flag[F_W], 1u); }
      const uint32_t grp = warp >> 2, kq = warp & 3;
      const uint32_t wo = sb + OFF_WO + grp * 36864 + kq * 512 + ((l3 >> 1) * 8 + l7) * 32 + (((l3 & 1) ^ (kq >> 1) ^ (l7 >> 2)) << 4);
      uint32_t f[2][12];
      if (warp >= 5) {
        const uint32_t g = warp - 5;
        const uint32_t r4 = sb + OFF_RA + g * 256 + (l3 >> 1) * 1024 + (lane & 15) * 16, r2 = sb + OFF_RA + g * 256 + 2048 + (lane & 15) * 16;
        mbar_wait(bar + B_A, s & 1);
        uint32_t t0, t1, t2, t3, t4, t5;
        ldsm4t(t0, t1, t2, t3, r4);
        asm volatile("ldmatrix.sync.aligned.m8n8.x2.trans.shared.b16 {%0,%1}, [%2];" : "=r"(t4), "=r"(t5) : "r"(r2) : "memory");
        float p0 = (__uint_as_float(t0 << 16) + __uint_as_float(t2 << 16)) + __uint_as_float(t4 << 16);
        float p1 = (__uint_as_float(t0 & 0xffff0000u) + __uint_as_float(t2 & 0xffff0000u)) + __uint_as_float(t4 & 0xffff0000u);
        float p2 = (__uint_as_float(t1 << 16) + __uint_as_float(t3 << 16)) + __uint_as_float(t5 << 16);
        float p3 = (__uint_as_float(t1 & 0xffff0000u) + __uint_as_float(t3 & 0xffff0000u)) + __uint_as_float(t5 & 0xffff0000u);
        if (g == 2) { p2 = -INFINITY; p3 = -INFINITY; }
        float mx = fmaxf(fmaxf(p0, p1), fmaxf(p2, p3));
        mx = fmaxf(mx, __shfl_xor_sync(~0u, mx, 1)); mx = fmaxf(mx, __shfl_xor_sync(~0u, mx, 2));
        mx *= sc;
        const uint32_t e0 = pack2(ex2(fmaf(p0, sc, -mx)), ex2(fmaf(p1, sc, -mx))), e1 = pack2(ex2(fmaf(p2, sc, -mx)), ex2(fmaf(p3, sc, -mx)));
        const uint32_t pw = sb + OFF_P + lane * 16;
        sts1u(pw + (g == 2 ? 512 : g * 4), e0);
        sts1u(pw + (g == 2 ? 1024 : 8 + g * 4), e1);
        sts1f(pw + 516 + g * 4, mx);
        bar_arrive(NB_PM, 224);
      }
      if (warp == 1 || warp == 2) {
        const uint32_t rb = mapa(sb, lane < CL ? lane : 0);
        bar_sync(NB_V2, 192);
        if (warp == 1 && lane < CL) st_async1(rb + OFF_BAR + B_DUMMY, 0u, rb + OFF_BAR + B_XF);
        if (warp == 2) {
          if (lane == 0) mbar_expect(bar + B_X, 40960);
          mbar_wait(bar + B_XF, s & 1);
          if (lane == 0) mbar_expect(bar + B_XF, CL * 4);
          const int c2 = rank + 6 * lane;
          if (c2 < 10) tma2d_mc(sb + OFF_H + c2 * 5120, &tm_x, c2 * 64, (s + 1) * 32, bar + B_X, (uint16_t)0x3f);
          __syncwarp();
        }
      }
      {
        const uint32_t og = sb + OFF_OG + kq * 256 + (lane ^ ((kq & 1) << 2)) * 8;
        float v[12];
#pragma unroll
        for (int i = 0; i < 12; i++) v[i] = 0.f;
        bar_sync(NB_V, 384);
        WO_PREFETCH();
        bar_sync(NB_TS, 384);
        const bool lead = grp == (uint32_t)(cluster & 1);
        if (!lead) bar_sync(NB_QK, 256);
#pragma unroll
        for (int u = 0; u < 3; u++) {
          if (u == 1 && lead) bar_arrive(NB_QK, 256);
          mbar_wait(bar + B_B + 8 * u, s & 1);
          const float2 o0 = lds2f(og + u * 2048), o1 = lds2f(og + u * 2048 + 1024);
#pragma unroll
          for (int h = 0; h < 2; h++) {
            uint32_t* ff = f[h];
#pragma unroll
            for (int i = 0; i < 3; i++)
              mma16816(v + 4 * i, ff[4 * i], ff[4 * i + 1], ff[4 * i + 2], ff[4 * i + 3], __float_as_uint(h ? o1.x : o0.x), __float_as_uint(h ? o1.y : o0.y));
            if (u < 2) {
#pragma unroll
              for (int i = 0; i < 3; i++) ldsm4t(ff[4 * i], ff[4 * i + 1], ff[4 * i + 2], ff[4 * i + 3], wo + (2 * u + 2 + h) * 2048 + i * 12288);
            }
          }
        }
        const uint32_t xb = sb + OFF_Q + grp * 4608;
#pragma unroll
        for (int i = 1; i < 4; i++) {
          const uint32_t x = xb + ((i ^ kq) * 3 + (i - 1)) * 384;
          sts2f(x + lane * 8, v[i], v[4 + i]); sts1f(x + 256 + lane * 4, v[8 + i]);
        }
        float4* o = g_acc + (s * ACC_CHUNKS + (2 * rank + grp) * 160 + kq * 32) + lane;
        const uint32_t y = xb + kq * 1152;
        bar_sync(NB_R + grp, 128);
        const float2 p0 = lds2f(y + lane * 8), p1 = lds2f(y + 384 + lane * 8), p2 = lds2f(y + 768 + lane * 8);
        const float q0 = lds1f(y + 256 + lane * 4), q1 = lds1f(y + 640 + lane * 4), q2 = lds1f(y + 1024 + lane * 4);
        red4(o, (v[0] + p0.x) + (p1.x + p2.x), (v[4] + p0.y) + (p1.y + p2.y), (v[8] + q0) + (q1 + q2), 1.0f);
      }
      bar_sync(NB_G, 384);
      token_qk<true>(a, s, sb, warp, lane0, zero);
    }
    cluster_sync();
  } else {
    asm volatile("setmaxnreg.dec.sync.aligned.u32 88;");
    const uint32_t lane0 = __shfl_xor_sync(~0u, opq((threadIdx.x & 31) ^ 1), 1);
    asm volatile("barrier.cluster.arrive.relaxed.aligned;" ::: "memory");
    uint32_t wv[4 * NRF];
    {
      const int i = tid0 - 256;
      mbar_wait(bar + B_WR, 0);
      const uint32_t l7 = lane0 & 7, l3 = lane0 >> 3;
#pragma unroll
      for (int k = 0; k < NRF; k++)
        ldsm4t(wv[4 * k], wv[4 * k + 1], wv[4 * k + 2], wv[4 * k + 3], sb + OFF_H + k * 2048 + ((l3 >> 1) * 8 + l7) * 128 + (((2 * (warp - 8) + (l3 & 1)) ^ l7) << 4));
      asm volatile("" :: "r"(wv[0]), "r"(wv[4]), "r"(wv[8]), "r"(wv[12]), "r"(wv[16]), "r"(wv[20]), "r"(wv[24]), "r"(wv[28]) : "memory");
      bar_sync(NB_P, 128);
#pragma unroll
      for (int r = 0; r < 5; r++) { const uint32_t j = i + r * 128; sts4u(memrow_addr(sb, (j % 80) * 8, j / 80), m0u[r]); }
      fence_async();
      if (i == 96) {
        wait_flag(&g_flag[F_LN], 96);
        for (int c = 0; c < 10; c++) tma2d(sb + OFF_H + c * 5120, &tm_x, c * 64, 0, bar + B_X);
      }
      __syncwarp();
    }
    mbar_wait(bar + B_W, 0);
    asm volatile("barrier.cluster.wait.acquire.aligned;" ::: "memory");
    const float sc = 0.07216878364870322f * 1.4426950408889634f;

    bar_arrive(NB_M, 384);
    for (int s = 0; s < NSEG; s++) {
      const bool last = s == NSEG - 1;
      uint32_t va[10];
      {
        uint32_t wt_[4 * NTP];
        {
          const uint32_t ln = opq(lane0), l7 = ln & 7, l3 = ln >> 3;
#pragma unroll
          for (int k = 0; k < NTP; k++)
            ldsm4t(wt_[4 * k], wt_[4 * k + 1], wt_[4 * k + 2], wt_[4 * k + 3],
                   sb + OFF_WV + (NSS - NTP + k) * 2048 + ((l3 >> 1) * 8 + l7) * 128 + (((2 * (warp - 8) + (l3 & 1)) ^ l7) << 4));
        }
        mbar_wait(bar + B_X, s & 1);
        float v[20];
        uint64_t db = mkdesc(sb + OFF_H, 16, 1024, 1), da = mkdesc(sb + OFF_WV, 1024, 1024, 1);
        OPAQUE64(db); OPAQUE64(da);
        uint64_t dk = mkdesc(sb + OFF_K, 16, 1024, 1), dq = mkdesc(sb + OFF_Q + 4096, 16, 1024, 1);
        OPAQUE64(dk); OPAQUE64(dq);
        const uint32_t ra = OFF_RA + j3 * 1024 + (warp - 8) * 256 + opq(lane0) * 4;
        float sm[4];
        bar_sync(NB_S, 384);
        WG_FENCE();
        wg_ss8<0>(sm, dk, dq); wg_ss8<1>(sm, dk + 2, dq + 2); wg_ss8<1>(sm, dk + 4, dq + 4); wg_ss8<1>(sm, dk + 6, dq + 6);
        WG_COMMIT();
        wg_ss40<0, 1>(v, da, db);
#pragma unroll
        for (int k = 1; k < VLEAD; k++) wg_ss40<1, 1>(v, da + (uint64_t)(k * 128), db + HOFF(k));
        WG_COMMIT();
        WG_WAIT(1);
        {
          const uint32_t x = pack2(sm[0], sm[1]), y = pack2(sm[2], sm[3]);
#pragma unroll
          for (int d = 0; d < 3; d++) {
            const uint32_t rb = mapa(sb, hb + (j3 + 1 + d) % 3);
            st_async1(rb + ra, x, rb + OFF_BAR + B_A); st_async1(rb + ra + 128, y, rb + OFF_BAR + B_A);
          }
        }
#pragma unroll
        for (int k = VLEAD; k < NSS - NTP; k++) wg_ss40<1, 1>(v, da + (uint64_t)(k * 128), db + HOFF(k));
#pragma unroll
        for (int k = 0; k < NTP; k++) wg_rs40<1>(v, wt_[4 * k], wt_[4 * k + 1], wt_[4 * k + 2], wt_[4 * k + 3], db + HOFF(NSS - NTP + k));
#pragma unroll
        for (int k = NSS; k < 40; k++) wg_rs40<1>(v, wv[4 * (k - NSS)], wv[4 * (k - NSS) + 1], wv[4 * (k - NSS) + 2], wv[4 * (k - NSS) + 3], db + HOFF(k));
        WG_COMMIT();
        WG_WAIT(0);
#pragma unroll
        for (int i = 0; i < 10; i++) va[i] = pack2(v[2 * i], v[2 * i + 1]);
      }
      const uint32_t lane = opq(lane0), w4 = warp - 8, wt = w4 * 32 + lane;
      if (!last) {
        bar_arrive(NB_V2, 192);
        bar_sync(NB_PM, 224);
        const uint4 pa = lds4u(sb + OFF_P + lane * 16), pc = lds4u(sb + OFF_P + 512 + lane * 16);
        float o[6][4], os[4], ot[4];
#pragma unroll
        for (int i = 0; i < 4; i++) { o[0][i] = o[1][i] = o[2][i] = o[3][i] = o[4][i] = o[5][i] = os[i] = ot[i] = 0.f; }
        mma16816(os, pa.x, pa.y, pa.z, pa.w, 0x3f803f80u, 0x3f803f80u);
        mma1688(ot, pc.x, pc.y, 0x3f803f80u);
        mma16816(o[0], pa.x, pa.y, pa.z, pa.w, va[0], va[2]);
        mma16816(o[1], pa.x, pa.y, pa.z, pa.w, va[1], va[3]);
        mma16816(o[2], pa.x, pa.y, pa.z, pa.w, va[4], va[6]);
        mma16816(o[3], pa.x, pa.y, pa.z, pa.w, va[5], va[7]);
        mma1688(o[4], pc.x, pc.y, va[8]);
        mma1688(o[5], pc.x, pc.y, va[9]);
        o[2][0] = o[2][2]; o[2][1] = o[2][3]; o[3][0] = o[3][2]; o[3][1] = o[3][3];
        const float ma = __uint_as_float(pc.y), mb = __uint_as_float(pc.z), mc = __uint_as_float(pc.w), mx = fmaxf(fmaxf(ma, mb), mc);
        float fa = ex2(ma - mx), fb = ex2(mb - mx), fc = ex2(mc - mx);
        const float inv = rcp(fmaf(fa, os[0], fmaf(fb, os[2], fc * ot[0])));
        fa *= inv; fb *= inv; fc *= inv;
        const uint32_t x = pack2(fmaf(fa, o[0][0], fmaf(fb, o[2][0], fc * o[4][0])), fmaf(fa, o[0][1], fmaf(fb, o[2][1], fc * o[4][1])));
        const uint32_t y = pack2(fmaf(fa, o[1][0], fmaf(fb, o[3][0], fc * o[5][0])), fmaf(fa, o[1][1], fmaf(fb, o[3][1], fc * o[5][1])));
#pragma unroll
        for (int d = 0; d < CL; d++) {
          int r = rank + d; if (r >= CL) r -= CL;
          const uint32_t rb = mapa(sb, r);
          st_async2(rb + OFF_OG + wt * 8 + d * 1024, x, y, rb + OFF_BAR + B_B + 8 * (d >> 1));
        }
        bar_arrive(NB_V, 384);
        if (wt == 0) mbar_expect(bar + B_A, 3 * 1024);
      }
      uint32_t e[5];
      {
        float v[20];
        uint64_t da = mkdesc(sb + OFF_Q, 16, 512, 1), db = mkdesc(sb + OFF_K, 16, 1024, 1);
        OPAQUE64(db); OPAQUE64(da);
        WG_FENCE();
        wg_ss40<0, 0>(v, da, db);
        wg_ss40<1, 0>(v, da + 2, db + 2);
        wg_ss40<1, 0>(v, da + 4, db + 4);
        wg_ss40<1, 0>(v, da + 6, db + 6);
        WG_COMMIT();
        WG_WAIT(0);
#pragma unroll
        for (int i = 0; i < 5; i++) e[i] = pack2(v[4 * i], v[4 * i + 1]);
      }
      if (!last) {
        bar_arrive(NB_TS, 384);
        if (w4 == 3) {
          if ((s & 3) == 0 && s > 0 && lane == 0) { __threadfence(); atomicAdd(&g_flag[(s >> 2) - 1], 1u); }
          __syncwarp();
        } else if (w4 != 0 && rank < 4) {
          if (s == 0) mbar_wait(bar + B_WO, 0);
          const uint32_t kh = w4 - 1, l7 = lane & 7, l3 = lane >> 3;
          const uint32_t wo = sb + OFF_WO + 6 * 12288 + kh * 2048 + ((l3 >> 1) * 8 + l7) * 32 + (((l3 & 1) ^ (l7 >> 2)) << 4);
          const uint32_t og = sb + OFF_OG + kh * 1024 + lane * 8;
          float u[4] = {0.f, 0.f, 0.f, 0.f};
#pragma unroll
          for (int it = 0; it < 3; it++) {
            uint32_t ff[16];
#pragma unroll
            for (int kk = 0; kk < 4; kk++) ldsm4t(ff[4 * kk], ff[4 * kk + 1], ff[4 * kk + 2], ff[4 * kk + 3], wo + it * 4096 + kk * 512);
            mbar_wait(bar + B_B + 8 * it, s & 1);
#pragma unroll
            for (int kk = 0; kk < 4; kk++) {
              const float2 o = lds2f(og + it * 2048 + kk * 256);
              mma16816(u, ff[4 * kk], ff[4 * kk + 1], ff[4 * kk + 2], ff[4 * kk + 3], __float_as_uint(o.x), __float_as_uint(o.y));
            }
          }
          const uint32_t xb = sb + OFF_RA + lane * 8;
          sts2f(xb + kh * 256, kh ? u[0] : u[2], kh ? u[1] : u[3]);
          float4* o = g_acc + (s * ACC_CHUNKS + (2 * rank + kh) * 160 + 128) + lane;
          bar_sync(NB_R + 2, 64);
          const float2 x = lds2f(xb + 256 - kh * 256);
          red4(o, (kh ? u[2] : u[0]) + x.x, (kh ? u[3] : u[1]) + x.y, 0.f, 1.0f);
        }
        bar_sync(NB_G, 384);
        if (wt < 3) mbar_expect(bar + B_B + 8 * wt, 2048);
      } else {
        mbar_wait(bar + B_A, s & 1);
      }
      {
#pragma unroll
        for (int d = 1; d <= 2; d++) {
          const uint32_t rb = mapa(sb, hb + (j3 + d) % 3);
          st_async4(rb + OFF_RT + (2 - d) * 2560 + wt * 16, e[0], e[1], e[2], e[3], rb + OFF_BAR + B_T);
          st_async1(rb + OFF_RT + (2 - d) * 2560 + 2048 + wt * 4, e[4], rb + OFF_BAR + B_T);
        }
      }
      mbar_wait(bar + B_T, s & 1);
      float p[10];
#pragma unroll
      for (int i = 0; i < 5; i++) { p[2 * i] = __uint_as_float(e[i] << 16); p[2 * i + 1] = __uint_as_float(e[i] & 0xffff0000u); }
#pragma unroll
      for (int d = 0; d < 2; d++) {
        const uint4 x = lds4u(sb + OFF_RT + d * 2560 + wt * 16);
        const uint32_t y = __float_as_uint(lds1f(sb + OFF_RT + d * 2560 + 2048 + wt * 4));
        p[0] += __uint_as_float(x.x << 16); p[1] += __uint_as_float(x.x & 0xffff0000u);
        p[2] += __uint_as_float(x.y << 16); p[3] += __uint_as_float(x.y & 0xffff0000u);
        p[4] += __uint_as_float(x.z << 16); p[5] += __uint_as_float(x.z & 0xffff0000u);
        p[6] += __uint_as_float(x.w << 16); p[7] += __uint_as_float(x.w & 0xffff0000u);
        p[8] += __uint_as_float(y << 16); p[9] += __uint_as_float(y & 0xffff0000u);
      }
      if (wt == 0) mbar_expect(bar + B_T, 2 * 2560);
      MemLoad<4> ml;
#pragma unroll
      for (int q = 0; q < 4; q++) ml.c[q] = make_float4(0.f, 0.f, 0.f, 0.f);
      if (!last) memload_issue(ml, s, warp, lane);
      {
        const int tq = 8 * w4 + (lane >> 2) - 2 * (lane & 3);
        float mx = fmaxf(p[8], p[9]);
#pragma unroll
        for (int i = 0; i < 8; i++) { if (8 * (i >> 1) + (i & 1) > tq) p[i] = -INFINITY; mx = fmaxf(mx, p[i]); }
        mx = fmaxf(mx, __shfl_xor_sync(~0u, mx, 1)); mx = fmaxf(mx, __shfl_xor_sync(~0u, mx, 2));
        float sum = 0.f;
#pragma unroll
        for (int i = 0; i < 10; i++) { p[i] = ex2(fmaf(p[i], sc, -mx * sc)); sum += p[i]; }
        sum += __shfl_xor_sync(~0u, sum, 1); sum += __shfl_xor_sync(~0u, sum, 2);
        const float inv = rcp(sum);
        const uint32_t pr = sb + OFF_P + (lane >> 3) * 800 + w4 * 32 + (lane & 7) * 4;
#pragma unroll
        for (int i = 0; i < 5; i++) sts1u(pr + i * 128, pack2(p[2 * i] * inv, p[2 * i + 1] * inv));
        sts1u(pr + 640, 0u);
      }
      if (!last) {
        memload_finish(ml, s, warp, lane, sb, (float)NCL);
        bar_arrive(NB_M, 384);
      }
      fence_async();
      bar_sync(NB_P, 128);
      {
        float o[16];
        uint64_t db = mkdesc(sb + OFF_P, 128, 800, 0);
        OPAQUE64(db);
        uint32_t vb[10];
#pragma unroll
        for (int i = 0; i < 10; i++) asm volatile("add.u32 %0, %1, %2;" : "=r"(vb[i]) : "r"(va[i]), "r"(zero));
        WG_FENCE();
        wg_rs32<0>(o, vb[0], vb[1], vb[2], vb[3], db);
        wg_rs32<1>(o, vb[4], vb[5], vb[6], vb[7], db + 16);
        wg_rs32<1>(o, vb[8], vb[9], 0u, 0u, db + 32);
        WG_COMMIT();
        uint4* dst = reinterpret_cast<uint4*>(g_oT) + ((s * HD + blockIdx.x * 64 + w4 * 16) * 4 + lane);
        WG_WAIT(0);
        dst[0] = make_uint4(pack2(o[0], o[1]), pack2(o[4], o[5]), pack2(o[8], o[9]), pack2(o[12], o[13]));
        dst[32] = make_uint4(pack2(o[2], o[3]), pack2(o[6], o[7]), pack2(o[10], o[11]), pack2(o[14], o[15]));
      }
    }
    bar_sync(NB_P, 128);
    if (tid0 == 256) { __threadfence(); atomicAdd(&g_flag[15], 1u); }
    cluster_sync();
  }
}

namespace hk {
constexpr int STAGES = 4, STAGE = 49152, OFF_ST = STAGES * STAGE, OFF_BAR = OFF_ST + 32768, SMEM = OFF_BAR + 1024, NCTA = NHELP;
constexpr int N_G1 = 192, SB0 = 12  , N_FULL = 5 * SB0, N_ITEMS = N_G1 + 20 + N_FULL + 5 * (2 + 4 + 7) + 1 + 35;
struct Item { int type, mb, nt, k0, k1, nsplit; };
__device__ __forceinline__ Item get_item(int i) {
  Item t;
  if (i < N_G1) { t.type = 0; t.mb = i / 12; t.nt = i % 12; t.k0 = 0; t.k1 = 10; t.nsplit = 1; return t; }
  i -= N_G1; t.type = 1; t.nt = i % 5;
  if (i < 20) { t.mb = SB0 + i / 5; t.k0 = 0; t.k1 = 24; t.nsplit = t.mb == 12 ? 3 : t.mb == 13 ? 5 : 8; return t; }
  i -= 20;
  if (i < N_FULL) { t.mb = i / 5; t.k0 = 0; t.k1 = 120; t.nsplit = 1; return t; }
  i -= N_FULL;
  int ns;
  if (i < 10) { t.mb = 12; ns = 2; } else if (i < 30) { i -= 10; t.mb = 13; ns = 4; } else if (i < 65) { i -= 30; t.mb = 14; ns = 7; }
  else if (i == 65) { t.type = 2; t.mb = t.k0 = t.k1 = 0; t.nsplit = 1; return t; }
  else { i -= 66; t.mb = 15; ns = 7; }
  t.nt = i % 5;
  const int p = i / 5;
  t.k0 = 24 + (96 * p) / ns; t.k1 = 24 + (96 * (p + 1)) / ns; t.nsplit = ns + 1;
  return t;
}
__device__ __forceinline__ void store_tile(const uint32_t* p, uint32_t stg, const CUtensorMap* tm, int c0, int r0, int wg, int t128) {
  const int lane = t128 & 31, r = (t128 >> 5) * 16 + (lane & 15);
  if (t128 == 0) asm volatile("cp.async.bulk.wait_group.read 0;" ::: "memory");
  bar_sync(1 + wg, 128);
#pragma unroll
  for (int j = 0; j < 8; j++) {
    const int c = 2 * j + (lane >> 4);
    const uint32_t a = stg + (c >> 3) * 8192 + r * 128 + (((c & 7) ^ (r & 7)) << 4);
    asm volatile("stmatrix.sync.aligned.m8n8.x4.shared.b16 [%0], {%1,%2,%3,%4};" :: "r"(a), "r"(p[4 * j]), "r"(p[4 * j + 1]), "r"(p[4 * j + 2]), "r"(p[4 * j + 3]) : "memory");
  }
  fence_async();
  bar_sync(1 + wg, 128);
  if (t128 == 0) {
    asm volatile("cp.async.bulk.tensor.2d.global.shared::cta.bulk_group [%0, {%2, %3}], [%1];" :: "l"(tm), "r"(stg), "r"(c0), "r"(r0) : "memory");
    asm volatile("cp.async.bulk.tensor.2d.global.shared::cta.bulk_group [%0, {%2, %3}], [%1];" :: "l"(tm), "r"(stg + 8192), "r"(c0 + 64), "r"(r0) : "memory");
    asm volatile("cp.async.bulk.commit_group;" ::: "memory");
  }
}
}
__global__ void __launch_bounds__(384, 1)
helper_kernel(const __grid_constant__ CUtensorMap tm_x, const __grid_constant__ CUtensorMap tm_g, const __grid_constant__ CUtensorMap tm_u,
              const __grid_constant__ CUtensorMap tm_h, const __grid_constant__ CUtensorMap tm_o, const __grid_constant__ CUtensorMap tm_wd,
              const __grid_constant__ CUtensorMap tm_wo, const __grid_constant__ CUtensorMap tm_hs, const __grid_constant__ CUtensorMap tm_out,
              const bf16* __restrict__ x) {
  using namespace hk;
  extern __shared__ __align__(1024) unsigned char smem[];
  const uint32_t sb = smem_u32(smem), bar = sb + OFF_BAR;
  const int tid = threadIdx.x, lane = tid & 31, wg = __shfl_sync(~0u, tid >> 7, 0);
  if (tid == 0) { for (int i = 0; i < STAGES; i++) { mbar_init(bar + 8 * i, 1); mbar_init(bar + 64 + 8 * i, 2); } asm volatile("fence.mbarrier_init.release.cluster;" ::: "memory"); }
  __syncthreads();
  const int i0 = blockIdx.x;
  if (wg == 2) {
    asm volatile("setmaxnreg.dec.sync.aligned.u32 40;");
    if (tid == 256) {
      uint32_t it = 0;
      wait_flag(&g_flag[F_LN], 96);
      wait_flag(&g_flag[F_W], 48);
      for (int i = i0; i < N_ITEMS; i += NCTA) {
        const Item t = get_item(i);
        const int m0 = t.mb * 128, n0 = t.nt * 128;
        int kb = t.k0;
        if (t.type == 1 && kb == 0) wait_flag(&g_flag[16 + t.mb], 24);
        for (; kb < t.k1 && kb < 24; kb++, it++) {
          const uint32_t st = it % STAGES, base = sb + st * STAGE, full = bar + 8 * st;
          mbar_wait_long(bar + 64 + 8 * st, ((it / STAGES) & 1) ^ 1);
          if (t.type == 0) {
            mbar_expect(full, 49152);
            tma2d(base, &tm_x, kb * 64, m0, full);
            tma2d(base + 16384, &tm_g, n0, kb * 64, full);
            tma2d(base + 24576, &tm_g, n0 + 64, kb * 64, full);
            tma2d(base + 32768, &tm_u, n0, kb * 64, full);
            tma2d(base + 40960, &tm_u, n0 + 64, kb * 64, full);
          } else {
            mbar_expect(full, 32768);
            tma2d(base, &tm_h, kb * 64, m0, full);
            tma2d(base + 16384, &tm_wd, n0, kb * 64, full);
            tma2d(base + 24576, &tm_wd, n0 + 64, kb * 64, full);
          }
        }
        const int kf = kb;
        for (; kb < t.k1; kb++, it++) {
          const uint32_t st = it % STAGES, base = sb + st * STAGE, full = bar + 8 * st;
          const int k0 = (kb - 24) * 64;
          mbar_wait_long(bar + 64 + 8 * st, ((it / STAGES) & 1) ^ 1);
          mbar_expect(full, 32768);
          tma2d(base + 16384, &tm_wo, n0, k0, full);
          tma2d(base + 24576, &tm_wo, n0 + 64, k0, full);
          if (kb == kf + STAGES - 2) {
            wait_flag(&g_flag[t.mb], 96);
            for (int j = STAGES - 2; j > 0; j--) tma3d(sb + ((it - j) % STAGES) * STAGE, &tm_o, 0, k0 - j * 64, m0 / 32, bar + 8 * ((it - j) % STAGES));
          }
          if (kb >= kf + STAGES - 2) tma3d(base, &tm_o, 0, k0, m0 / 32, full);
        }
      }
    }
  } else {
    asm volatile("setmaxnreg.inc.sync.aligned.u32 232;");
    uint32_t it = 0;
    for (int i = i0; i < N_ITEMS; i += NCTA) {
      const Item t = get_item(i);
      const int row = t.mb * 128 + wg * 64 + ((tid >> 5) & 3) * 16 + (lane >> 2);
      if (t.type == 2) continue;
      if (t.type == 0) {
        float dg[64], du[64];
#pragma unroll
        for (int j = 0; j < 64; j++) { dg[j] = 0.f; du[j] = 0.f; }
        for (int kb = 0; kb < 10; kb++, it++) {
          const uint32_t st = it % STAGES, base = sb + st * STAGE;
          mbar_wait_long(bar + 8 * st, (it / STAGES) & 1);
          const uint64_t da = mkdesc(base + wg * 8192, 16, 1024, 1), db = mkdesc(base + 16384, 8192, 1024, 1);
          WG_FENCE();
#pragma unroll
          for (int k = 0; k < 4; k++) { wg_ss128<0>(dg, da + 2 * k, db + 128 * k); wg_ss128<0>(du, da + 2 * k, db + 1024 + 128 * k); }
          WG_COMMIT();
          WG_WAIT(1);
          if (kb > 0 && (tid & 127) == 0) mbar_arrive(bar + 64 + 8 * ((it - 1) % STAGES));
        }
        WG_WAIT(0);
        if ((tid & 127) == 0) mbar_arrive(bar + 64 + 8 * ((it - 1) % STAGES));
        uint32_t p[32];
#pragma unroll
        for (int j = 0; j < 32; j++) p[j] = pack2(bfr(dg[2 * j]) * bfr(du[2 * j]), bfr(dg[2 * j + 1]) * bfr(du[2 * j + 1]));
        store_tile(p, sb + OFF_ST + wg * 16384, &tm_hs, t.nt * 128, t.mb * 128 + wg * 64, wg, tid & 127);
        if ((tid & 127) == 0) {
          asm volatile("cp.async.bulk.wait_group 0;" ::: "memory");
          asm volatile("fence.proxy.async;" ::: "memory");
          __threadfence(); atomicAdd(&g_flag[16 + t.mb], 1u);
        }
      } else {
        float d[64];
#pragma unroll
        for (int j = 0; j < 64; j++) d[j] = 0.f;
        uint32_t xr[32];
        {
          const uint32_t* xi = reinterpret_cast<const uint32_t*>(x + (size_t)row * DM + t.nt * 128 + (lane & 3) * 2);
#pragma unroll
          for (int j = 0; j < 16; j++) { xr[2 * j] = __ldg(xi + j * 4); xr[2 * j + 1] = __ldg(xi + j * 4 + 4 * DM); }
        }
        int kb = t.k0;
        for (; kb < t.k1 && kb < 24; kb++, it++) {
          const uint32_t st = it % STAGES, base = sb + st * STAGE;
          mbar_wait_long(bar + 8 * st, (it / STAGES) & 1);
          const uint64_t da = mkdesc(base + wg * 8192, 16, 1024, 1), db = mkdesc(base + 16384, 8192, 1024, 1);
          WG_FENCE();
#pragma unroll
          for (int k = 0; k < 4; k++) wg_ss128<0>(d, da + 2 * k, db + 128 * k);
          WG_COMMIT();
          WG_WAIT(1);
          if (kb > t.k0 && (tid & 127) == 0) mbar_arrive(bar + 64 + 8 * ((it - 1) % STAGES));
        }
        WG_WAIT(0);
        for (; kb < t.k1; kb++, it++) {
          const uint32_t st = it % STAGES, base = sb + st * STAGE;
          mbar_wait_long(bar + 8 * st, (it / STAGES) & 1);
          const uint64_t da = mkdesc(base + wg * 8192, 4096, 512, 2), db = mkdesc(base + 16384, 8192, 1024, 1);
          WG_FENCE();
#pragma unroll
          for (int k = 0; k < 4; k++) wg_ss128<1>(d, da + 64 * k, db + 128 * k);
          WG_COMMIT();
          WG_WAIT(1);
          if (kb > t.k0 && (tid & 127) == 0) mbar_arrive(bar + 64 + 8 * ((it - 1) % STAGES));
        }
        WG_WAIT(0);
        if ((tid & 127) == 0) mbar_arrive(bar + 64 + 8 * ((it - 1) % STAGES));
        {
          const uint32_t m = t.k0 == 0 ? 0xffff0000u : 0u;
#pragma unroll
          for (int j = 0; j < 32; j++) { d[2 * j] += __uint_as_float((xr[j] << 16) & m); d[2 * j + 1] += __uint_as_float(xr[j] & m); }
        }
        bool fin = true;
        if (t.nsplit > 1) {
          const int ti = (t.mb - SB0) * 5 + t.nt;
          float4* pp = g_part + ti * 4096 + tid;
#pragma unroll
          for (int j = 0; j < 16; j++) red4(pp + j * 256, d[4 * j], d[4 * j + 1], d[4 * j + 2], d[4 * j + 3]);
          bar_sync(1 + wg, 128);
          volatile unsigned* sflag = reinterpret_cast<volatile unsigned*>(smem + OFF_BAR + 256 + wg * 4);
          if ((tid & 127) == 0) {
            __threadfence();
            const unsigned old = atomicAdd(&g_flag[32 + ti], wg ? 0x10000u : 1u);
            *sflag = ((wg ? old >> 16 : old & 0xffffu) == (unsigned)t.nsplit - 1);
            __threadfence();
          }
          bar_sync(1 + wg, 128);
          fin = __shfl_sync(~0u, *sflag, 0) != 0;
          if (fin) {
#pragma unroll
            for (int j = 0; j < 16; j++) {
              const float4 u = __ldcg(pp + j * 256);
              d[4 * j] = u.x; d[4 * j + 1] = u.y; d[4 * j + 2] = u.z; d[4 * j + 3] = u.w;
            }
          }
        }
        if (fin) {
          uint32_t p[32];
#pragma unroll
          for (int j = 0; j < 32; j++) p[j] = pack2(d[2 * j], d[2 * j + 1]);
          store_tile(p, sb + OFF_ST + wg * 16384, &tm_out, t.nt * 128, t.mb * 128 + wg * 64, wg, tid & 127);
        }
      }
    }
    bar_sync(3, 256);
    if (tid >= 32 && tid < 64) {
      asm volatile("griddepcontrol.wait;" ::: "memory");
      unsigned old = 0;
      if (lane == 0) old = atomicAdd(&g_flag[F_DONE], 1u);
      if (__shfl_sync(~0u, old, 0) == NCTA - 1) { g_flag[lane] = 0; g_flag[32 + lane] = 0; }
    }
    if ((tid & 127) == 0) asm volatile("cp.async.bulk.wait_group 0;" ::: "memory");
  }
}

__global__ void fb_ln(const bf16* __restrict__ x) {
  uint2 u[5];
  const int row = blockIdx.x * 8 + (threadIdx.x >> 5), lane = threadIdx.x & 31;
  for (int j = 0; j < 5; j++) u[j] = reinterpret_cast<const uint2*>(x + (size_t)row * DM)[j * 32 + lane];
  ln_row(u, row, lane);
}
__global__ void fb_gemm(const bf16* A0, const bf16* A1, int m_split, const bf16* B, bf16* C0, bf16* C1, int N, int K, int mode, const bf16* R0, const bf16* R1) {
  const int n = blockIdx.x * blockDim.x + threadIdx.x, m = blockIdx.y;
  const bf16* a = m < m_split ? A0 + (size_t)m * K : A1 + (size_t)(m - m_split) * K;
  bf16* c = (m < m_split ? C0 + (size_t)m * N : C1 + (size_t)(m - m_split) * N) + n;
  float acc = 0.f;
  for (int k = 0; k < K; k++) acc += __bfloat162float(a[k]) * __bfloat162float(B[(size_t)k * N + n]);
  if (mode == 1) acc = bfr(acc) * __bfloat162float(*c);
  if (mode == 2) acc += __bfloat162float(R0[(size_t)m * N + n]) + __bfloat162float(R1[(size_t)m * N + n]);
  *c = __float2bfloat16_rn(acc);
}
__global__ void fb_attn(const bf16* q, const bf16* k, const bf16* v, bf16* o) {
  const int h = blockIdx.x, r = blockIdx.y, t = threadIdx.x;
  __shared__ float p[40];
  if (t < 40) {
    float a = 0.f;
    for (int e = 0; e < 192; e++) a += __bfloat162float(q[r * HD + h * 192 + e]) * __bfloat162float(k[t * HD + h * 192 + e]);
    p[t] = (r < 8 || r >= t) ? a * 0.07216878364870322f : -INFINITY;
  }
  __syncthreads();
  float mx = p[0], sum = 0.f, a = 0.f;
  for (int i = 1; i < 40; i++) mx = fmaxf(mx, p[i]);
  for (int i = 0; i < 40; i++) sum += __expf(p[i] - mx);
  for (int i = 0; i < 40; i++) a += bfr(__expf(p[i] - mx) / sum) * __bfloat162float(v[i * HD + h * 192 + t]);
  o[r * HD + h * 192 + t] = __float2bfloat16_rn(a);
}

typedef CUresult (*EncodeFn)(CUtensorMap*, CUtensorMapDataType, cuuint32_t, void*, const cuuint64_t*, const cuuint64_t*, const cuuint32_t*,
                             const cuuint32_t*, CUtensorMapInterleave, CUtensorMapSwizzle, CUtensorMapL2promotion, CUtensorMapFloatOOBfill);
static void make_map(EncodeFn enc, CUtensorMap* m, const void* p, int rank, const cuuint64_t* dims, const cuuint64_t* strides,
                     const cuuint32_t* box, CUtensorMapSwizzle swz) {
  cuuint32_t es[3] = {1, 1, 1};
  enc(m, CU_TENSOR_MAP_DATA_TYPE_BFLOAT16, rank, const_cast<void*>(p), dims, strides, box, es, CU_TENSOR_MAP_INTERLEAVE_NONE, swz,
      CU_TENSOR_MAP_L2_PROMOTION_L2_128B, CU_TENSOR_MAP_FLOAT_OOB_FILL_NONE);
}
static void map2d(EncodeFn enc, CUtensorMap* m, const void* p, int cols, int rows, int bc, int br, CUtensorMapSwizzle swz) {
  cuuint64_t dims[2] = {(cuuint64_t)cols, (cuuint64_t)rows}, strides[1] = {(cuuint64_t)cols * 2};
  cuuint32_t box[2] = {(cuuint32_t)bc, (cuuint32_t)br};
  make_map(enc, m, p, 2, dims, strides, box, swz);
}

extern "C" void kernel_launch(void* const* d_in, const int* in_sizes, int n_in, void* d_out, int out_size) {
  const bf16* x = (const bf16*)d_in[0];
  const bf16* mem0 = (const bf16*)d_in[1];
  const bf16* Wq = (const bf16*)d_in[2];
  const bf16* Wk = (const bf16*)d_in[3];
  const bf16* Wv = (const bf16*)d_in[4];
  const bf16* Wo = (const bf16*)d_in[5];
  const bf16* Wg = (const bf16*)d_in[8];
  const bf16* Wu = (const bf16*)d_in[9];
  const bf16* Wd = (const bf16*)d_in[10];
  bf16* out = (bf16*)d_out;

  void* fn = nullptr; cudaDriverEntryPointQueryResult qr;
  cudaGetDriverEntryPoint("cuTensorMapEncodeTiled", &fn, cudaEnableDefault, &qr);
  EncodeFn enc = (EncodeFn)fn;
  void *p_xn, *p_oT, *p_h;
  cudaGetSymbolAddress(&p_xn, g_xn); cudaGetSymbolAddress(&p_oT, g_oT); cudaGetSymbolAddress(&p_h, g_h);

  CUtensorMap t_x32, t_wv, t_wo16, t_x128, t_wg, t_wu, t_h, t_o, t_wd, t_wo64, t_hs, t_out, t_wq, t_wk;
  map2d(enc, &t_wq, Wq, HD, DM, 64, 128, CU_TENSOR_MAP_SWIZZLE_128B);
  map2d(enc, &t_wk, Wk, HD, DM, 64, 128, CU_TENSOR_MAP_SWIZZLE_128B);
  map2d(enc, &t_hs, p_h, FF, SEQ, 64, 64, CU_TENSOR_MAP_SWIZZLE_128B);
  map2d(enc, &t_out, out, DM, SEQ, 64, 64, CU_TENSOR_MAP_SWIZZLE_128B);
  map2d(enc, &t_x32, p_xn, DM, SEQ, 64, 32, CU_TENSOR_MAP_SWIZZLE_128B);
  map2d(enc, &t_wv, Wv, HD, DM, 64, 128, CU_TENSOR_MAP_SWIZZLE_128B);
  map2d(enc, &t_wo16, Wo, DM, HD, 16, 64, CU_TENSOR_MAP_SWIZZLE_32B);
  map2d(enc, &t_x128, p_xn, DM, SEQ, 64, 128, CU_TENSOR_MAP_SWIZZLE_128B);
  map2d(enc, &t_wg, Wg, FF, DM, 64, 64, CU_TENSOR_MAP_SWIZZLE_128B);
  map2d(enc, &t_wu, Wu, FF, DM, 64, 64, CU_TENSOR_MAP_SWIZZLE_128B);
  map2d(enc, &t_h, p_h, FF, SEQ, 64, 128, CU_TENSOR_MAP_SWIZZLE_128B);
  map2d(enc, &t_wd, Wd, DM, FF, 64, 64, CU_TENSOR_MAP_SWIZZLE_128B);
  map2d(enc, &t_wo64, Wo, DM, HD, 64, 64, CU_TENSOR_MAP_SWIZZLE_128B);
  {
    cuuint64_t dims[3] = {32, (cuuint64_t)HD, (cuuint64_t)NSEG}, strides[2] = {64, (cuuint64_t)HD * 64};
    cuuint32_t box[3] = {32, 64, 4};
    make_map(enc, &t_o, p_oT, 3, dims, strides, box, CU_TENSOR_MAP_SWIZZLE_64B);
  }
  cudaFuncSetAttribute(chain_kernel, cudaFuncAttributeMaxDynamicSharedMemorySize, ck::SMEM);
  cudaFuncSetAttribute(helper_kernel, cudaFuncAttributeMaxDynamicSharedMemorySize, hk::SMEM);

  cudaStream_t st = cudaStreamPerThread;
  {
    cudaLaunchConfig_t cfg = {};
    cfg.gridDim = dim3(ck::CL * ck::NCL); cfg.blockDim = dim3(384); cfg.dynamicSmemBytes = ck::SMEM; cfg.stream = st;
    cudaLaunchAttribute at[1];
    at[0].id = cudaLaunchAttributeClusterDimension; at[0].val.clusterDim.x = ck::CL; at[0].val.clusterDim.y = 1; at[0].val.clusterDim.z = 1;
    cfg.attrs = at; cfg.numAttrs = 1;
    int ncl = 0;
    if (cudaOccupancyMaxActiveClusters(&ncl, chain_kernel, &cfg) != cudaSuccess) { (void)cudaGetLastError(); ncl = 0; }
    if (ncl < ck::NCL) {
      bf16 *xn = (bf16*)p_xn, *h = (bf16*)p_h, *q = (bf16*)p_oT, *k = q + 40 * HD, *v = k + 40 * HD, *o = v + 40 * HD, *mem = o + 40 * HD, *att = mem + 8 * DM;
      fb_ln<<<SEQ / 8, 256, 0, st>>>(x);
      for (int s = 0; s < NSEG; s++) {
        const bf16 *m = s ? mem : mem0, *xs = xn + s * 32 * DM;
        fb_gemm<<<dim3(HD / 128, 40), 128, 0, st>>>(m, xs, 8, Wq, q, q + 8 * HD, HD, DM, 0, nullptr, nullptr);
        fb_gemm<<<dim3(HD / 128, 40), 128, 0, st>>>(m, xs, 8, Wk, k, k + 8 * HD, HD, DM, 0, nullptr, nullptr);
        fb_gemm<<<dim3(HD / 128, 40), 128, 0, st>>>(m, xs, 8, Wv, v, v + 8 * HD, HD, DM, 0, nullptr, nullptr);
        fb_attn<<<dim3(32, 40), 192, 0, st>>>(q, k, v, o);
        fb_gemm<<<dim3(DM / 128, 40), 128, 0, st>>>(o, o + 8 * HD, 8, Wo, mem, att + s * 32 * DM, DM, HD, 0, nullptr, nullptr);
      }
      fb_gemm<<<dim3(FF / 128, SEQ), 128, 0, st>>>(xn, xn, SEQ, Wg, h, h, FF, DM, 0, nullptr, nullptr);
      fb_gemm<<<dim3(FF / 128, SEQ), 128, 0, st>>>(xn, xn, SEQ, Wu, h, h, FF, DM, 1, nullptr, nullptr);
      fb_gemm<<<dim3(DM / 128, SEQ), 128, 0, st>>>(h, h, SEQ, Wd, out, out, DM, FF, 2, x, att);
      return;
    }
    cudaLaunchKernelEx(&cfg, chain_kernel, t_x32, t_wv, t_wo16, t_wq, t_wk, mem0, x, 0u);
  }
  {
    cudaLaunchConfig_t cfg = {};
    cfg.gridDim = dim3(hk::NCTA); cfg.blockDim = dim3(384); cfg.dynamicSmemBytes = hk::SMEM; cfg.stream = st;
    cudaLaunchAttribute at[1];
    at[0].id = cudaLaunchAttributeProgrammaticStreamSerialization; at[0].val.programmaticStreamSerializationAllowed = 1;
    cfg.attrs = at; cfg.numAttrs = 1;
    cudaLaunchKernelEx(&cfg, helper_kernel, t_x128, t_wg, t_wu, t_h, t_o, t_wd, t_wo64, t_hs, t_out, x);
  }
}
```

```cpp
#include <cuda_runtime.h>
#include <cuda_bf16.h>
#include <cuda.h>
#include <stdint.h>

typedef __nv_bfloat16 bf16;

constexpr int SEQ = 2048, DM = 640, HD = 6144, FF = 1536, NSEG = 64;
constexpr int ACC_CHUNKS = 1920;

__device__ __align__(1024) bf16 g_xn[SEQ * DM];
__device__ __align__(1024) bf16 g_oT[NSEG * HD * 32];
__device__ __align__(1024) bf16 g_h[SEQ * FF];
__device__ __align__(1024) float4 g_acc[NSEG * ACC_CHUNKS];
__device__ __align__(1024) float4 g_part[20 * 4096];
__device__ unsigned g_flag[64];

__device__ __forceinline__ uint32_t smem_u32(const void* p) { return (uint32_t)__cvta_generic_to_shared(p); }
__device__ __forceinline__ uint32_t mapa(uint32_t a, uint32_t r) { uint32_t o; asm("mapa.shared::cluster.u32 %0, %1, %2;" : "=r"(o) : "r"(a), "r"(r)); return o; }
__device__ __forceinline__ void mbar_init(uint32_t b, int c) { asm volatile("mbarrier.init.shared::cta.b64 [%0], %1;" :: "r"(b), "r"(c) : "memory"); }
__device__ __forceinline__ void mbar_expect(uint32_t b, uint32_t bytes) { asm volatile("mbarrier.arrive.expect_tx.shared::cta.b64 _, [%0], %1;" :: "r"(b), "r"(bytes) : "memory"); }
__device__ __forceinline__ void mbar_arrive(uint32_t b) { asm volatile("mbarrier.arrive.shared::cta.b64 _, [%0];" :: "r"(b) : "memory"); }
constexpr int SPIN_LIMIT = 1 << 20;
__device__ __forceinline__ void mbar_wait(uint32_t b, uint32_t ph) {
  asm volatile("{\n.reg .pred p;\n.reg .u32 n;\nmov.u32 n, 0;\n"
               "W: mbarrier.try_wait.parity.shared::cta.b64 p, [%0], %1;\n@p bra D;\n"
               "add.u32 n, n, 1;\nsetp.lt.u32 p, n, 0x40000;\n@p bra W;\ntrap;\nD:\n}" :: "r"(b), "r"(ph) : "memory");
}
__device__ __forceinline__ void mbar_wait_long(uint32_t b, uint32_t ph) {
  asm volatile("{\n.reg .pred p;\n.reg .u32 n;\nmov.u32 n, 0;\n"
               "W: mbarrier.try_wait.parity.shared::cta.b64 p, [%0], %1;\n@p bra D;\n"
               "add.u32 n, n, 1;\nsetp.lt.u32 p, n, 0x400000;\n@p bra W;\ntrap;\nD:\n}" :: "r"(b), "r"(ph) : "memory");
}
__device__ __forceinline__ void bar_sync(int id, int n) { asm volatile("bar.sync %0, %1;" :: "r"(id), "r"(n) : "memory"); }
__device__ __forceinline__ void bar_arrive(int id, int n) { asm volatile("bar.arrive %0, %1;" :: "r"(id), "r"(n) : "memory"); }
__device__ __forceinline__ void fence_async() { asm volatile("fence.proxy.async.shared::cta;" ::: "memory"); }
__device__ __forceinline__ void cluster_sync() { asm volatile("barrier.cluster.arrive.release.aligned;\nbarrier.cluster.wait.acquire.aligned;" ::: "memory"); }
__device__ __forceinline__ void tma2d(uint32_t dst, const CUtensorMap* m, int c0, int c1, uint32_t bar) {
  asm volatile("cp.async.bulk.tensor.2d.shared::cluster.global.mbarrier::complete_tx::bytes [%0], [%1, {%3, %4}], [%2];"
               :: "r"(dst), "l"(m), "r"(bar), "r"(c0), "r"(c1) : "memory");
}
__device__ __forceinline__ void tma2d_mc(uint32_t dst, const CUtensorMap* m, int c0, int c1, uint32_t bar, uint16_t mask) {
  asm volatile("cp.async.bulk.tensor.2d.shared::cluster.global.mbarrier::complete_tx::bytes.multicast::cluster [%0], [%1, {%3, %4}], [%2], %5;"
               :: "r"(dst), "l"(m), "r"(bar), "r"(c0), "r"(c1), "h"(mask) : "memory");
}
__device__ __forceinline__ void tma3d(uint32_t dst, const CUtensorMap* m, int c0, int c1, int c2, uint32_t bar) {
  asm volatile("cp.async.bulk.tensor.3d.shared::cluster.global.mbarrier::complete_tx::bytes [%0], [%1, {%3, %4, %5}], [%2];"
               :: "r"(dst), "l"(m), "r"(bar), "r"(c0), "r"(c1), "r"(c2) : "memory");
}
__device__ __forceinline__ void st_async1(uint32_t a, uint32_t x, uint32_t mb) {
  asm volatile("st.async.weak.shared::cluster.mbarrier::complete_tx::bytes.b32 [%0], %1, [%2];" :: "r"(a), "r"(x), "r"(mb) : "memory");
}
__device__ __forceinline__ void st_async2(uint32_t a, uint32_t x, uint32_t y, uint32_t mb) {
  asm volatile("st.async.weak.shared::cluster.mbarrier::complete_tx::bytes.v2.b32 [%0], {%1,%2}, [%3];" :: "r"(a), "r"(x), "r"(y), "r"(mb) : "memory");
}
__device__ __forceinline__ void st_async4(uint32_t a, uint32_t x, uint32_t y, uint32_t z, uint32_t w, uint32_t mb) {
  asm volatile("st.async.weak.shared::cluster.mbarrier::complete_tx::bytes.v4.b32 [%0], {%1,%2,%3,%4}, [%5];" :: "r"(a), "r"(x), "r"(y), "r"(z), "r"(w), "r"(mb) : "memory");
}
__device__ __forceinline__ void ldsm4(uint32_t& r0, uint32_t& r1, uint32_t& r2, uint32_t& r3, uint32_t a) {
  asm volatile("ldmatrix.sync.aligned.m8n8.x4.shared.b16 {%0,%1,%2,%3}, [%4];" : "=r"(r0), "=r"(r1), "=r"(r2), "=r"(r3) : "r"(a) : "memory");
}
__device__ __forceinline__ void ldsm4t(uint32_t& r0, uint32_t& r1, uint32_t& r2, uint32_t& r3, uint32_t a) {
  asm volatile("ldmatrix.sync.aligned.m8n8.x4.trans.shared.b16 {%0,%1,%2,%3}, [%4];" : "=r"(r0), "=r"(r1), "=r"(r2), "=r"(r3) : "r"(a) : "memory");
}
__device__ __forceinline__ void stsm4t(uint32_t a, uint32_t r0, uint32_t r1, uint32_t r2, uint32_t r3) {
  asm volatile("stmatrix.sync.aligned.m8n8.x4.trans.shared.b16 [%0], {%1,%2,%3,%4};" :: "r"(a), "r"(r0), "r"(r1), "r"(r2), "r"(r3) : "memory");
}
__device__ __forceinline__ void stsm1t(uint32_t a, uint32_t r0) {
  asm volatile("stmatrix.sync.aligned.m8n8.x1.trans.shared.b16 [%0], {%1};" :: "r"(a), "r"(r0) : "memory");
}
__device__ __forceinline__ void stsm2t(uint32_t a, uint32_t r0, uint32_t r1) {
  asm volatile("stmatrix.sync.aligned.m8n8.x2.trans.shared.b16 [%0], {%1,%2};" :: "r"(a), "r"(r0), "r"(r1) : "memory");
}
__device__ __forceinline__ void mma16816(float* d, uint32_t a0, uint32_t a1, uint32_t a2, uint32_t a3, uint32_t b0, uint32_t b1) {
  asm volatile("mma.sync.aligned.m16n8k16.row.col.f32.bf16.bf16.f32 {%0,%1,%2,%3}, {%4,%5,%6,%7}, {%8,%9}, {%0,%1,%2,%3};"
               : "+f"(d[0]), "+f"(d[1]), "+f"(d[2]), "+f"(d[3]) : "r"(a0), "r"(a1), "r"(a2), "r"(a3), "r"(b0), "r"(b1));
}
__device__ __forceinline__ void mma1688(float* d, uint32_t a0, uint32_t a1, uint32_t b0) {
  asm volatile("mma.sync.aligned.m16n8k8.row.col.f32.bf16.bf16.f32 {%0,%1,%2,%3}, {%4,%5}, {%6}, {%0,%1,%2,%3};"
               : "+f"(d[0]), "+f"(d[1]), "+f"(d[2]), "+f"(d[3]) : "r"(a0), "r"(a1), "r"(b0));
}
__device__ __forceinline__ float ex2(float x) { float r; asm("ex2.approx.ftz.f32 %0, %1;" : "=f"(r) : "f"(x)); return r; }
__device__ __forceinline__ float rcp(float x) { float r; asm("rcp.approx.ftz.f32 %0, %1;" : "=f"(r) : "f"(x)); return r; }
__device__ __forceinline__ uint32_t pack2(float lo, float hi) { uint32_t r; asm("cvt.rn.bf16x2.f32 %0, %1, %2;" : "=r"(r) : "f"(hi), "f"(lo)); return r; }
__device__ __forceinline__ float2 lds2f(uint32_t a) { float2 v; asm volatile("ld.shared.v2.f32 {%0,%1}, [%2];" : "=f"(v.x), "=f"(v.y) : "r"(a) : "memory"); return v; }
__device__ __forceinline__ float4 lds4f(uint32_t a) { float4 v; asm volatile("ld.shared.v4.f32 {%0,%1,%2,%3}, [%4];" : "=f"(v.x), "=f"(v.y), "=f"(v.z), "=f"(v.w) : "r"(a) : "memory"); return v; }
__device__ __forceinline__ uint4 lds4u(uint32_t a) { uint4 v; asm volatile("ld.shared.v4.u32 {%0,%1,%2,%3}, [%4];" : "=r"(v.x), "=r"(v.y), "=r"(v.z), "=r"(v.w) : "r"(a) : "memory"); return v; }
__device__ __forceinline__ float lds1f(uint32_t a) { float v; asm volatile("ld.shared.f32 %0, [%1];" : "=f"(v) : "r"(a) : "memory"); return v; }
__device__ __forceinline__ void sts4f(uint32_t a, float x, float y, float z, float w) { asm volatile("st.shared.v4.f32 [%0], {%1,%2,%3,%4};" :: "r"(a), "f"(x), "f"(y), "f"(z), "f"(w) : "memory"); }
__device__ __forceinline__ void sts2f(uint32_t a, float x, float y) { asm volatile("st.shared.v2.f32 [%0], {%1,%2};" :: "r"(a), "f"(x), "f"(y) : "memory"); }
__device__ __forceinline__ void sts1f(uint32_t a, float x) { asm volatile("st.shared.f32 [%0], %1;" :: "r"(a), "f"(x) : "memory"); }
__device__ __forceinline__ void sts1u(uint32_t a, uint32_t x) { asm volatile("st.shared.u32 [%0], %1;" :: "r"(a), "r"(x) : "memory"); }
__device__ __forceinline__ void sts4u(uint32_t a, uint4 v) { asm volatile("st.shared.v4.u32 [%0], {%1,%2,%3,%4};" :: "r"(a), "r"(v.x), "r"(v.y), "r"(v.z), "r"(v.w) : "memory"); }
__device__ __forceinline__ float4 ld_relaxed4(const float4* p) {
  float4 r; asm volatile("ld.relaxed.gpu.global.v4.f32 {%0,%1,%2,%3}, [%4];" : "=f"(r.x), "=f"(r.y), "=f"(r.z), "=f"(r.w) : "l"(p) : "memory"); return r;
}
__device__ __forceinline__ void red4(float4* p, float a, float b, float c, float d) {
  asm volatile("red.relaxed.gpu.global.add.v4.f32 [%0], {%1,%2,%3,%4};" :: "l"(p), "f"(a), "f"(b), "f"(c), "f"(d) : "memory");
}
__device__ __forceinline__ uint64_t mkdesc(uint32_t addr, uint32_t lbo, uint32_t sbo, uint32_t swz) {
  return (uint64_t)((addr & 0x3FFFF) >> 4) | ((uint64_t)(lbo >> 4) << 16) | ((uint64_t)(sbo >> 4) << 32) | ((uint64_t)swz << 62);
}
#define WG_FENCE() asm volatile("wgmma.fence.sync.aligned;" ::: "memory")
#define WG_COMMIT() asm volatile("wgmma.commit_group.sync.aligned;" ::: "memory")
#define WG_WAIT(n) asm volatile("wgmma.wait_group.sync.aligned %0;" :: "n"(n) : "memory")
#define OPAQUE64(x) asm volatile("" : "+l"(x))

#define F4(d, i) "+f"(d[i]), "+f"(d[i + 1]), "+f"(d[i + 2]), "+f"(d[i + 3])
#define F16(d, i) F4(d, i), F4(d, i + 4), F4(d, i + 8), F4(d, i + 12)
template <int ACC>
__device__ __forceinline__ void wg_rs32(float* d, uint32_t a0, uint32_t a1, uint32_t a2, uint32_t a3, uint64_t b) {
  asm volatile("wgmma.mma_async.sync.aligned.m64n32k16.f32.bf16.bf16 {%0,%1,%2,%3,%4,%5,%6,%7,%8,%9,%10,%11,%12,%13,%14,%15}, {%16,%17,%18,%19}, %20, %21, 1, 1, 0;"
               : F16(d, 0) : "r"(a0), "r"(a1), "r"(a2), "r"(a3), "l"(b), "n"(ACC));
}
template <int ACC>
__device__ __forceinline__ void wg_rs32x(float* d, uint32_t a0, uint32_t a1, uint32_t a2, uint32_t a3, uint32_t blo) {
  asm volatile("{\n.reg .b64 b;\nmov.b64 b, {%20, 0x40000040};\n"
               "wgmma.mma_async.sync.aligned.m64n32k16.f32.bf16.bf16 {%0,%1,%2,%3,%4,%5,%6,%7,%8,%9,%10,%11,%12,%13,%14,%15}, {%16,%17,%18,%19}, b, %21, 1, 1, 0;\n}"
               : F16(d, 0) : "r"(a0), "r"(a1), "r"(a2), "r"(a3), "r"(blo), "n"(ACC));
}
template <int ACC>
__device__ __forceinline__ void wg_rs40(float* d, uint32_t a0, uint32_t a1, uint32_t a2, uint32_t a3, uint64_t b) {
  asm volatile("wgmma.mma_async.sync.aligned.m64n40k16.f32.bf16.bf16 {%0,%1,%2,%3,%4,%5,%6,%7,%8,%9,%10,%11,%12,%13,%14,%15,%16,%17,%18,%19}, {%20,%21,%22,%23}, %24, %25, 1, 1, 0;"
               : F16(d, 0), F4(d, 16) : "r"(a0), "r"(a1), "r"(a2), "r"(a3), "l"(b), "n"(ACC));
}
template <int ACC>
__device__ __forceinline__ void wg_ss8(float* d, uint64_t a, uint64_t b) {
  asm volatile("wgmma.mma_async.sync.aligned.m64n8k16.f32.bf16.bf16 {%0,%1,%2,%3}, %4, %5, %6, 1, 1, 0, 0;" : F4(d, 0) : "l"(a), "l"(b), "n"(ACC));
}
template <int ACC, int TA>
__device__ __forceinline__ void wg_ss40(float* d, uint64_t a, uint64_t b) {
  asm volatile("wgmma.mma_async.sync.aligned.m64n40k16.f32.bf16.bf16 {%0,%1,%2,%3,%4,%5,%6,%7,%8,%9,%10,%11,%12,%13,%14,%15,%16,%17,%18,%19}, %20, %21, %22, 1, 1, %23, 0;"
               : F16(d, 0), F4(d, 16) : "l"(a), "l"(b), "n"(ACC), "n"(TA));
}
template <int TA>
__device__ __forceinline__ void wg_ss128(float* d, uint64_t a, uint64_t b) {
  asm volatile("wgmma.mma_async.sync.aligned.m64n128k16.f32.bf16.bf16 {"
               "%0,%1,%2,%3,%4,%5,%6,%7,%8,%9,%10,%11,%12,%13,%14,%15,%16,%17,%18,%19,%20,%21,%22,%23,%24,%25,%26,%27,%28,%29,%30,%31,"
               "%32,%33,%34,%35,%36,%37,%38,%39,%40,%41,%42,%43,%44,%45,%46,%47,%48,%49,%50,%51,%52,%53,%54,%55,%56,%57,%58,%59,%60,%61,%62,%63"
               "}, %64, %65, 1, 1, 1, %66, 1;"
               : F16(d, 0), F16(d, 16), F16(d, 32), F16(d, 48) : "l"(a), "l"(b), "n"(TA));
}

__device__ __forceinline__ float bfr(float x) { return __bfloat162float(__float2bfloat16_rn(x)); }
constexpr int F_LN = 52, F_DONE = 53, F_W = 54, NHELP = 36;
__device__ __forceinline__ void ln_row(const uint2 (&u)[5], int row, int lane) {
  float v[20];
#pragma unroll
  for (int i = 0; i < 5; i++) {
    v[4 * i + 0] = __uint_as_float(u[i].x << 16); v[4 * i + 1] = __uint_as_float(u[i].x & 0xffff0000u);
    v[4 * i + 2] = __uint_as_float(u[i].y << 16); v[4 * i + 3] = __uint_as_float(u[i].y & 0xffff0000u);
  }
  float s = 0.f;
#pragma unroll
  for (int i = 0; i < 20; i++) s += v[i];
#pragma unroll
  for (int o = 16; o; o >>= 1) s += __shfl_xor_sync(~0u, s, o);
  const float mean = s * (1.0f / DM);
  float q = 0.f;
#pragma unroll
  for (int i = 0; i < 20; i++) { float d = v[i] - mean; q += d * d; }
#pragma unroll
  for (int o = 16; o; o >>= 1) q += __shfl_xor_sync(~0u, q, o);
  const float mb = bfr(mean), rs = 1.0f / bfr(sqrtf(bfr(bfr(q * (1.0f / DM)) + 1e-5f)));
  uint2* dst = reinterpret_cast<uint2*>(g_xn + (size_t)row * DM);
#pragma unroll
  for (int i = 0; i < 5; i++) {
    uint2 o;
    o.x = pack2(bfr(v[4 * i + 0] - mb) * rs, bfr(v[4 * i + 1] - mb) * rs);
    o.y = pack2(bfr(v[4 * i + 2] - mb) * rs, bfr(v[4 * i + 3] - mb) * rs);
    dst[i * 32 + lane] = o;
  }
}
__device__ __forceinline__ void wait_flag(const unsigned* f, unsigned target) {
  unsigned v; int n = 0;
  while (true) {
    asm volatile("ld.acquire.gpu.global.u32 %0, [%1];" : "=r"(v) : "l"(f) : "memory");
    if (v >= target) break;
    if (++n > (1 << 21)) __trap();
    __nanosleep(100);
  }
  asm volatile("fence.proxy.async.global;" ::: "memory");
}

namespace ck {
constexpr int CL = 6, NCL = 16, NRF = 8, NSS = 40 - NRF, NTP = 1;
constexpr uint32_t OFF_H = 0, OFF_WV = 51200, OFF_WO = OFF_WV + NSS * 2048, OFF_Q = OFF_WO + 86016, OFF_K = OFF_Q + 5120,
                   OFF_OG = OFF_K + 5120, OFF_RA = OFF_OG + 6144, OFF_P = OFF_RA + 3840, OFF_RT = OFF_P + 3200,
                   OFF_BAR = OFF_RT + 5120, SMEM = OFF_BAR + 256;
constexpr uint32_t B_X = 0, B_A = 8, B_T = 16, B_W = 24, B_WR = 32, B_B = 40  , B_XF = 88, B_DUMMY = 96, B_WO = 104,
                   B_ST = 128  ;
enum { NB_M = 1, NB_QK = 2, NB_PM = 3, NB_V = 4, NB_TS = 5, NB_P = 6, NB_G = 7, NB_R = 8  , NB_S = 12, NB_V2 = 13, NB_G1 = 14 };
static_assert(SMEM <= 232448, "smem");
static_assert(OFF_WO % 1024 == 0 && OFF_Q % 1024 == 0, "align");
}
__device__ __forceinline__ uint32_t opq(uint32_t x) { asm volatile("" : "+r"(x)); return x; }

__device__ __forceinline__ uint32_t memrow_addr(uint32_t sb, uint32_t col0, uint32_t m) {
  return sb + ck::OFF_H + (col0 >> 6) * 5120 + 4096 + m * 128 + ((((col0 >> 3) & 7) ^ m) << 4);
}
constexpr int VLEAD = 5;
constexpr int LW = 24, LW2 = 33;
constexpr int DEPTH = 2;
template <int N> struct MemLoad { float4 c[N]; };
template <int N>
__device__ __forceinline__ void memload_issue(MemLoad<N>& m, int s, uint32_t warp, uint32_t lane) {
  const float4* p = g_acc + (s * ACC_CHUNKS + warp * 160) + lane;
#pragma unroll
  for (int q = 0; q < N; q++) m.c[q] = ld_relaxed4(p + q * 32);
}
template <int N>
__device__ __forceinline__ void memload_finish(MemLoad<N>& m, int s, uint32_t warp, uint32_t lane0, uint32_t sb, float full) {
  const uint32_t lane = opq(lane0);
  const uint32_t a4 = memrow_addr(sb, warp * 48 + (lane >> 3) * 8, lane & 7), a2 = memrow_addr(sb, warp * 48 + 32 + ((lane >> 3) & 1) * 8, lane & 7);
  const uint32_t a1 = memrow_addr(sb, 576 + warp * 8, lane & 7);
  int n = 0;
  while (true) {
    bool ok = true;
#pragma unroll
    for (int q = 0; q < N; q++) ok = ok && m.c[q].w == full;
    if (__all_sync(~0u, ok)) break;
    if (++n > SPIN_LIMIT) __trap();
    memload_issue(m, s, warp, opq(lane0));
  }
  const float4* c = m.c;
  stsm4t(a4, pack2(c[0].x, c[1].x), pack2(c[2].x, c[3].x), pack2(c[0].y, c[1].y), pack2(c[2].y, c[3].y));
  stsm2t(a2, pack2(c[0].z, c[1].z), pack2(c[2].z, c[3].z));
  if (N == 5) stsm1t(a1, pack2(c[N - 1].x, c[N - 1].y + c[N - 1].z));
}
#define WO_PREFETCH() _Pragma("unroll") for (int i = 0; i < 6; i++) \
  ldsm4t(f[i / 3][4 * (i % 3)], f[i / 3][4 * (i % 3) + 1], f[i / 3][4 * (i % 3) + 2], f[i / 3][4 * (i % 3) + 3], wo + (i % 3) * 12288 + (i / 3) * 2048)
#define HOFF(k) ((uint64_t)((((k) >> 2) * 5120 + ((k) & 3) * 32) >> 4))

template <bool LOADS>
__device__ __forceinline__ void token_qk(const uint32_t* a, int s, uint32_t sb, uint32_t warp, uint32_t lane0, uint32_t zero, bool lead) {
  using namespace ck;
  const uint32_t bar = sb + OFF_BAR;
  float d[16];
  MemLoad<5> ml;
  mbar_wait(bar + B_X, (s + 1) & 1);
  const uint32_t db = opq((uint32_t)mkdesc(sb + OFF_H, 16, 1024, 1));
  WG_FENCE();
  wg_rs32x<0>(d, a[0], a[1], a[2], a[3], db);
#pragma unroll
  for (int k = 1; k < 40; k++) {
    wg_rs32x<1>(d, a[4 * k], a[4 * k + 1], a[4 * k + 2], a[4 * k + 3], db + (uint32_t)HOFF(k));
    if (LOADS && (k == LW || k == LW2)) WG_COMMIT();
  }
  WG_COMMIT();
  if (LOADS) { WG_WAIT(2); if (lead) WG_WAIT(1); do { memload_issue(ml, s, warp, opq(lane0)); } while (zero >> 31); }
  WG_WAIT(0);
  const uint32_t e0 = pack2(d[0], d[1]);
  const uint32_t lane = opq(lane0), wg = warp >> 2, w4 = warp & 3;
  const uint32_t mat = lane >> 3, i = lane & 7, h = mat & 1, j0 = mat >> 1;
  const uint32_t ep0 = sb + OFF_Q + wg * 5120 + (8 * j0 + i) * 128 + (((2 * w4 + h) ^ i) << 4), ep1 = ep0 + 2048;
  stsm4t(ep0, e0, pack2(d[2], d[3]), pack2(d[4], d[5]), pack2(d[6], d[7]));
  stsm4t(ep1, pack2(d[8], d[9]), pack2(d[10], d[11]), pack2(d[12], d[13]), pack2(d[14], d[15]));
  if (LOADS) memload_finish(ml, s, warp, lane, sb, __uint_as_float(__float_as_uint((float)NCL) + (e0 & zero)));
}

__global__ void __launch_bounds__(384, 1)
chain_kernel(const __grid_constant__ CUtensorMap tm_x, const __grid_constant__ CUtensorMap tm_wv, const __grid_constant__ CUtensorMap tm_wo,
             const __grid_constant__ CUtensorMap tm_wq, const __grid_constant__ CUtensorMap tm_wk, const bf16* __restrict__ mem0,
             const bf16* __restrict__ x, uint32_t zero) {
  using namespace ck;
  extern __shared__ __align__(1024) unsigned char smem[];
  const uint32_t sb = smem_u32(smem);
  const uint32_t tid0 = threadIdx.x;
  const uint32_t warp = __shfl_sync(~0u, threadIdx.x >> 5, 0);
  const int rank = blockIdx.x % CL, cluster = blockIdx.x / CL;
  const int hb = (rank / 3) * 3, j3 = rank % 3;
  const uint32_t bar = sb + OFF_BAR;

  asm volatile("griddepcontrol.launch_dependents;");
  const int gw = (tid0 >> 5) * 96 + blockIdx.x;
  uint2 xu[2][5];
  uint4 m0u[5];
#pragma unroll
  for (int r = 0; r < 5; r++) m0u[r] = __ldg(reinterpret_cast<const uint4*>(mem0) + (tid0 & 127) + r * 128);
#pragma unroll
  for (int r = 0; r < 2; r++) {
    const int row = min(gw + r * 1152, SEQ - 1);
#pragma unroll
    for (int j = 0; j < 5; j++) xu[r][j] = __ldg(reinterpret_cast<const uint2*>(x + (size_t)row * DM) + j * 32 + (tid0 & 31));
  }
  if (tid0 == 0) {
    mbar_init(bar + B_X, 1); mbar_init(bar + B_A, 1); mbar_init(bar + B_T, 1); mbar_init(bar + B_W, 1); mbar_init(bar + B_WR, 1);
    for (int i = 0; i < 3; i++) mbar_init(bar + B_B + 8 * i, 1);
    for (int i = 0; i < 10; i++) mbar_init(bar + B_ST + 8 * i, 1);
    mbar_init(bar + B_XF, 1); mbar_init(bar + B_WO, 1);
    asm volatile("fence.mbarrier_init.release.cluster;" ::: "memory");
    mbar_expect(bar + B_A, 3 * 1024); mbar_expect(bar + B_T, 2 * 2560);
    for (int i = 0; i < 3; i++) mbar_expect(bar + B_B + 8 * i, 2048);
    for (int i = 0; i < 10; i++) mbar_expect(bar + B_ST + 8 * i, 16384);
    mbar_expect(bar + B_XF, CL * 4);
    mbar_expect(bar + B_X, 40960);
    mbar_expect(bar + B_WR, NRF * 2048);
    mbar_expect(bar + B_W, NSS * 2048); mbar_expect(bar + B_WO, (rank < 4 ? 7 : 6) * 12288);
    tma2d(sb + OFF_H, &tm_wv, blockIdx.x * 64, NSS * 16, bar + B_WR);
  }
  {
    const float4 z = make_float4(0.f, 0.f, 0.f, 0.f);
    for (int j = blockIdx.x * 384 + tid0; j < NSEG * ACC_CHUNKS; j += 96 * 384) g_acc[j] = z;
    for (int j = blockIdx.x * 384 + tid0; j < 20 * 4096; j += 96 * 384) g_part[j] = z;
  }
#pragma unroll 1
  for (int r = 0; r < 2; r++) {
    if (gw + r * 1152 < SEQ) ln_row(xu[0], gw + r * 1152, tid0 & 31);
#pragma unroll
    for (int j = 0; j < 5; j++) xu[0][j] = xu[1][j];
    if (r == 0 && tid0 < 2 * DEPTH) {
      const uint32_t wg = tid0 & 1, i = tid0 >> 1;
      tma2d(sb + (wg == 0 ? OFF_WO + i * 16384 : i < 4 ? OFF_WV + i * 16384 : OFF_Q), wg == 0 ? &tm_wq : &tm_wk, blockIdx.x * 64, i * 128,
            bar + B_ST + 8 * (wg * 5 + i));
    }
    __syncwarp();
  }
  __threadfence();
  __syncthreads();
  if (tid0 == 320) atomicAdd(&g_flag[F_LN], 1u);

  if (warp < 8) {
    asm volatile("setmaxnreg.inc.sync.aligned.u32 208;");
    const uint32_t lane0 = __shfl_sync(~0u, opq(threadIdx.x & 31), threadIdx.x & 31);
    uint32_t a[160];
    {
      const uint32_t wg = warp >> 2, l7 = lane0 & 7, l3 = lane0 >> 3, t128 = tid0 & 127;
      const uint32_t lo = ((l3 >> 1) * 8 + l7) * 128 + (((2 * (warp & 3) + (l3 & 1)) ^ l7) << 4);
#pragma unroll
      for (int i = 0; i < 5; i++) {
        const uint32_t base = sb + (wg == 0 ? OFF_WO + i * 16384 : i < 4 ? OFF_WV + i * 16384 : OFF_Q) + lo;
        mbar_wait(bar + B_ST + 8 * (wg * 5 + i), 0);
        if (i + DEPTH < 5 && t128 == 0)
          tma2d(sb + (wg == 0 ? OFF_WO + (i + DEPTH) * 16384 : i + DEPTH < 4 ? OFF_WV + (i + DEPTH) * 16384 : OFF_Q), wg == 0 ? &tm_wq : &tm_wk,
                blockIdx.x * 64, (i + DEPTH) * 128, bar + B_ST + 8 * (wg * 5 + i + DEPTH));
        __syncwarp();
#pragma unroll
        for (int k = 0; k < 8; k++) ldsm4t(a[32 * i + 4 * k], a[32 * i + 4 * k + 1], a[32 * i + 4 * k + 2], a[32 * i + 4 * k + 3], base + k * 2048);
        asm volatile("" :: "r"(a[32 * i]), "r"(a[32 * i + 4]), "r"(a[32 * i + 8]), "r"(a[32 * i + 12]), "r"(a[32 * i + 16]), "r"(a[32 * i + 20]), "r"(a[32 * i + 24]), "r"(a[32 * i + 28]) : "memory");
        bar_sync(NB_R + wg, 128);
        if (wg == 1) {
          if (i >= 3 && t128 < 2) tma2d(sb + OFF_WV + ((i - 3) * 2 + t128) * 16384, &tm_wv, blockIdx.x * 64, ((i - 3) * 2 + t128) * 128, bar + B_W);
        } else if (i == 4) {
          const int t = t128 / 6, d = t128 % 6;
          if (t < (rank < 4 ? 7 : 6)) tma2d(sb + OFF_WO + t * 12288 + d * 2048, &tm_wo, t < 6 ? rank * 96 + t * 16 : 576 + rank * 16,
                                            cluster * 384 + ((rank + CL - d) % CL) * 64, bar + B_WO);
        }
        __syncwarp();
      }
      bar_sync(NB_QK, 256);
      asm volatile("barrier.cluster.arrive.relaxed.aligned;" ::: "memory");
    }
    token_qk<false>(a, -1, sb, warp, lane0, zero, false);
    asm volatile("barrier.cluster.wait.acquire.aligned;" ::: "memory");
    const float sc = 0.07216878364870322f * 1.4426950408889634f;

    for (int s = 0;; s++) {
      uint32_t lane;
      {
        const uint32_t ln = opq(lane0);
        const uint32_t x0 = sb + OFF_H + 4096 + (ln & 7) * 128 + (((ln >> 3) ^ (ln & 7)) << 4), x1 = x0 ^ 64;
        float c[16];
#pragma unroll
        for (int i = 0; i < 16; i++) c[i] = 0.f;
        uint32_t bf[1][16];
        bar_sync(NB_M, 384);
#pragma unroll
        for (int k = 0; k < 40; k += 2) {
          uint32_t* b = bf[0] + 12;
          ldsm4(b[0], b[1], b[2], b[3], ((k & 2) ? x1 : x0) + (k >> 2) * 5120);
          float* d = c + ((k & 2) ? 8 : 0);
          mma16816(d, a[4 * k], a[4 * k + 1], a[4 * k + 2], a[4 * k + 3], b[0], b[1]);
          mma16816(d + 4, a[4 * k + 4], a[4 * k + 5], a[4 * k + 6], a[4 * k + 7], b[2], b[3]);
        }
#pragma unroll
        for (int i = 0; i < 4; i++) c[i] = (c[i] + c[4 + i]) + (c[8 + i] + c[12 + i]);
        asm volatile("add.u32 %0, %1, %2;" : "=r"(lane) : "r"(lane0), "r"(bf[0][15] & zero));
        const uint32_t qst = sb + OFF_Q + (warp >> 2) * 5120 + (32 + (lane & 7)) * 128 + (((2 * (warp & 3) + ((lane >> 3) & 1)) ^ (lane & 7)) << 4);
        stsm2t(qst, pack2(c[0], c[1]), pack2(c[2], c[3]));
      }
      const uint32_t l7 = lane & 7, l3 = lane >> 3;
      fence_async();
      bar_arrive(NB_S, 384);
      if (s == NSEG - 1) break;
      if (s == 0) { mbar_wait(bar + B_WO, 0); if (tid0 == 64) atomicAdd(&g_flag[F_W], 1u); }
      const uint32_t grp = warp >> 2, kq = warp & 3;
      const uint32_t wo = sb + OFF_WO + grp * 36864 + kq * 512 + ((l3 >> 1) * 8 + l7) * 32 + (((l3 & 1) ^ (kq >> 1) ^ (l7 >> 2)) << 4);
      uint32_t f[2][12];
      if (warp >= 5) {
        const uint32_t g = warp - 5;
        const uint32_t r4 = sb + OFF_RA + g * 256 + (l3 >> 1) * 1024 + (lane & 15) * 16, r2 = sb + OFF_RA + g * 256 + 2048 + (lane & 15) * 16;
        mbar_wait(bar + B_A, s & 1);
        uint32_t t0, t1, t2, t3, t4, t5;
        ldsm4t(t0, t1, t2, t3, r4);
        asm volatile("ldmatrix.sync.aligned.m8n8.x2.trans.shared.b16 {%0,%1}, [%2];" : "=r"(t4), "=r"(t5) : "r"(r2) : "memory");
        float p0 = (__uint_as_float(t0 << 16) + __uint_as_float(t2 << 16)) + __uint_as_float(t4 << 16);
        float p1 = (__uint_as_float(t0 & 0xffff0000u) + __uint_as_float(t2 & 0xffff0000u)) + __uint_as_float(t4 & 0xffff0000u);
        float p2 = (__uint_as_float(t1 << 16) + __uint_as_float(t3 << 16)) + __uint_as_float(t5 << 16);
        float p3 = (__uint_as_float(t1 & 0xffff0000u) + __uint_as_float(t3 & 0xffff0000u)) + __uint_as_float(t5 & 0xffff0000u);
        if (g == 2) { p2 = -INFINITY; p3 = -INFINITY; }
        float mx = fmaxf(fmaxf(p0, p1), fmaxf(p2, p3));
        mx = fmaxf(mx, __shfl_xor_sync(~0u, mx, 1)); mx = fmaxf(mx, __shfl_xor_sync(~0u, mx, 2));
        mx *= sc;
        const uint32_t e0 = pack2(ex2(fmaf(p0, sc, -mx)), ex2(fmaf(p1, sc, -mx))), e1 = pack2(ex2(fmaf(p2, sc, -mx)), ex2(fmaf(p3, sc, -mx)));
        const uint32_t pw = sb + OFF_P + lane * 16;
        sts1u(pw + (g == 2 ? 512 : g * 4), e0);
        sts1u(pw + (g == 2 ? 1024 : 8 + g * 4), e1);
        sts1f(pw + 516 + g * 4, mx);
        bar_arrive(NB_PM, 224);
      }
      if (warp == 1 || warp == 2) {
        const uint32_t rb = mapa(sb, lane < CL ? lane : 0);
        bar_sync(NB_V2, 192);
        if (warp == 1 && lane < CL) st_async1(rb + OFF_BAR + B_DUMMY, 0u, rb + OFF_BAR + B_XF);
        if (warp == 2) {
          if (lane == 0) mbar_expect(bar + B_X, 40960);
          mbar_wait(bar + B_XF, s & 1);
          if (lane == 0) mbar_expect(bar + B_XF, CL * 4);
          const int c2 = rank + 6 * lane;
          if (c2 < 10) tma2d_mc(sb + OFF_H + c2 * 5120, &tm_x, c2 * 64, (s + 1) * 32, bar + B_X, (uint16_t)0x3f);
          __syncwarp();
        }
      }
      {
        const uint32_t og = sb + OFF_OG + kq * 256 + (lane ^ ((kq & 1) << 2)) * 8;
        float v[12];
#pragma unroll
        for (int i = 0; i < 12; i++) v[i] = 0.f;
        bar_sync(NB_V, 384);
        WO_PREFETCH();
        bar_sync(NB_TS, 384);
        const bool lead = grp == (uint32_t)(cluster & 1);
        if (!lead) bar_sync(NB_QK, 256);
#pragma unroll
        for (int u = 0; u < 3; u++) {
          if (u == 1 && lead) bar_arrive(NB_QK, 256);
          mbar_wait(bar + B_B + 8 * u, s & 1);
          const float2 o0 = lds2f(og + u * 2048), o1 = lds2f(og + u * 2048 + 1024);
#pragma unroll
          for (int h = 0; h < 2; h++) {
            uint32_t* ff = f[h];
#pragma unroll
            for (int i = 0; i < 3; i++)
              mma16816(v + 4 * i, ff[4 * i], ff[4 * i + 1], ff[4 * i + 2], ff[4 * i + 3], __float_as_uint(h ? o1.x : o0.x), __float_as_uint(h ? o1.y : o0.y));
            if (u < 2) {
#pragma unroll
              for (int i = 0; i < 3; i++) ldsm4t(ff[4 * i], ff[4 * i + 1], ff[4 * i + 2], ff[4 * i + 3], wo + (2 * u + 2 + h) * 2048 + i * 12288);
            }
          }
        }
        const uint32_t xb = sb + OFF_Q + grp * 4608;
#pragma unroll
        for (int i = 1; i < 4; i++) {
          const uint32_t x = xb + ((i ^ kq) * 3 + (i - 1)) * 384;
          sts2f(x + lane * 8, v[i], v[4 + i]); sts1f(x + 256 + lane * 4, v[8 + i]);
        }
        if (!lead) bar_arrive(NB_G1, 384);
        float4* o = g_acc + (s * ACC_CHUNKS + (2 * rank + grp) * 160 + kq * 32) + lane;
        const uint32_t y = xb + kq * 1152;
        bar_sync(NB_R + grp, 128);
        const float2 p0 = lds2f(y + lane * 8), p1 = lds2f(y + 384 + lane * 8), p2 = lds2f(y + 768 + lane * 8);
        const float q0 = lds1f(y + 256 + lane * 4), q1 = lds1f(y + 640 + lane * 4), q2 = lds1f(y + 1024 + lane * 4);
        red4(o, (v[0] + p0.x) + (p1.x + p2.x), (v[4] + p0.y) + (p1.y + p2.y), (v[8] + q0) + (q1 + q2), 1.0f);
      }
      if (grp == (uint32_t)(cluster & 1)) { bar_arrive(NB_G, 384); bar_sync(NB_G1, 384); }
      else bar_sync(NB_G, 384);
      token_qk<true>(a, s, sb, warp, lane0, zero, grp == (uint32_t)(cluster & 1));
    }
    cluster_sync();
  } else {
    asm volatile("setmaxnreg.dec.sync.aligned.u32 88;");
    const uint32_t lane0 = __shfl_xor_sync(~0u, opq((threadIdx.x & 31) ^ 1), 1);
    asm volatile("barrier.cluster.arrive.relaxed.aligned;" ::: "memory");
    uint32_t wv[4 * NRF];
    {
      const int i = tid0 - 256;
      mbar_wait(bar + B_WR, 0);
      const uint32_t l7 = lane0 & 7, l3 = lane0 >> 3;
#pragma unroll
      for (int k = 0; k < NRF; k++)
        ldsm4t(wv[4 * k], wv[4 * k + 1], wv[4 * k + 2], wv[4 * k + 3], sb + OFF_H + k * 2048 + ((l3 >> 1) * 8 + l7) * 128 + (((2 * (warp - 8) + (l3 & 1)) ^ l7) << 4));
      asm volatile("" :: "r"(wv[0]), "r"(wv[4]), "r"(wv[8]), "r"(wv[12]), "r"(wv[16]), "r"(wv[20]), "r"(wv[24]), "r"(wv[28]) : "memory");
      bar_sync(NB_P, 128);
#pragma unroll
      for (int r = 0; r < 5; r++) { const uint32_t j = i + r * 128; sts4u(memrow_addr(sb, (j % 80) * 8, j / 80), m0u[r]); }
      fence_async();
      if (i == 96) {
        wait_flag(&g_flag[F_LN], 96);
        for (int c = 0; c < 10; c++) tma2d(sb + OFF_H + c * 5120, &tm_x, c * 64, 0, bar + B_X);
      }
      __syncwarp();
    }
    mbar_wait(bar + B_W, 0);
    asm volatile("barrier.cluster.wait.acquire.aligned;" ::: "memory");
    const float sc = 0.07216878364870322f * 1.4426950408889634f;

    bar_arrive(NB_M, 384);
    for (int s = 0; s < NSEG; s++) {
      const bool last = s == NSEG - 1;
      uint32_t va[10];
      {
        uint32_t wt_[4 * NTP];
        {
          const uint32_t ln = opq(lane0), l7 = ln & 7, l3 = ln >> 3;
#pragma unroll
          for (int k = 0; k < NTP; k++)
            ldsm4t(wt_[4 * k], wt_[4 * k + 1], wt_[4 * k + 2], wt_[4 * k + 3],
                   sb + OFF_WV + (NSS - NTP + k) * 2048 + ((l3 >> 1) * 8 + l7) * 128 + (((2 * (warp - 8) + (l3 & 1)) ^ l7) << 4));
        }
        mbar_wait(bar + B_X, s & 1);
        float v[20];
        uint64_t db = mkdesc(sb + OFF_H, 16, 1024, 1), da = mkdesc(sb + OFF_WV, 1024, 1024, 1);
        OPAQUE64(db); OPAQUE64(da);
        uint64_t dk = mkdesc(sb + OFF_K, 16, 1024, 1), dq = mkdesc(sb + OFF_Q + 4096, 16, 1024, 1);
        OPAQUE64(dk); OPAQUE64(dq);
        const uint32_t ra = OFF_RA + j3 * 1024 + (warp - 8) * 256 + opq(lane0) * 4;
        float sm[4];
        bar_sync(NB_S, 384);
        WG_FENCE();
        wg_ss8<0>(sm, dk, dq); wg_ss8<1>(sm, dk + 2, dq + 2); wg_ss8<1>(sm, dk + 4, dq + 4); wg_ss8<1>(sm, dk + 6, dq + 6);
        WG_COMMIT();
        wg_ss40<0, 1>(v, da, db);
#pragma unroll
        for (int k = 1; k < VLEAD; k++) wg_ss40<1, 1>(v, da + (uint64_t)(k * 128), db + HOFF(k));
        WG_COMMIT();
        WG_WAIT(1);
        {
          const uint32_t x = pack2(sm[0], sm[1]), y = pack2(sm[2], sm[3]);
#pragma unroll
          for (int d = 0; d < 3; d++) {
            const uint32_t rb = mapa(sb, hb + (j3 + 1 + d) % 3);
            st_async1(rb + ra, x, rb + OFF_BAR + B_A); st_async1(rb + ra + 128, y, rb + OFF_BAR + B_A);
          }
        }
#pragma unroll
        for (int k = VLEAD; k < NSS - NTP; k++) wg_ss40<1, 1>(v, da + (uint64_t)(k * 128), db + HOFF(k));
#pragma unroll
        for (int k = 0; k < NTP; k++) wg_rs40<1>(v, wt_[4 * k], wt_[4 * k + 1], wt_[4 * k + 2], wt_[4 * k + 3], db + HOFF(NSS - NTP + k));
#pragma unroll
        for (int k = NSS; k < 40; k++) wg_rs40<1>(v, wv[4 * (k - NSS)], wv[4 * (k - NSS) + 1], wv[4 * (k - NSS) + 2], wv[4 * (k - NSS) + 3], db + HOFF(k));
        WG_COMMIT();
        WG_WAIT(0);
#pragma unroll
        for (int i = 0; i < 10; i++) va[i] = pack2(v[2 * i], v[2 * i + 1]);
      }
      const uint32_t lane = opq(lane0), w4 = warp - 8, wt = w4 * 32 + lane;
      if (!last) {
        bar_arrive(NB_V2, 192);
        bar_sync(NB_PM, 224);
        const uint4 pa = lds4u(sb + OFF_P + lane * 16), pc = lds4u(sb + OFF_P + 512 + lane * 16);
        float o[6][4], os[4], ot[4];
#pragma unroll
        for (int i = 0; i < 4; i++) { o[0][i] = o[1][i] = o[2][i] = o[3][i] = o[4][i] = o[5][i] = os[i] = ot[i] = 0.f; }
        mma16816(os, pa.x, pa.y, pa.z, pa.w, 0x3f803f80u, 0x3f803f80u);
        mma1688(ot, pc.x, pc.y, 0x3f803f80u);
        mma16816(o[0], pa.x, pa.y, pa.z, pa.w, va[0], va[2]);
        mma16816(o[1], pa.x, pa.y, pa.z, pa.w, va[1], va[3]);
        mma16816(o[2], pa.x, pa.y, pa.z, pa.w, va[4], va[6]);
        mma16816(o[3], pa.x, pa.y, pa.z, pa.w, va[5], va[7]);
        mma1688(o[4], pc.x, pc.y, va[8]);
        mma1688(o[5], pc.x, pc.y, va[9]);
        o[2][0] = o[2][2]; o[2][1] = o[2][3]; o[3][0] = o[3][2]; o[3][1] = o[3][3];
        const float ma = __uint_as_float(pc.y), mb = __uint_as_float(pc.z), mc = __uint_as_float(pc.w), mx = fmaxf(fmaxf(ma, mb), mc);
        float fa = ex2(ma - mx), fb = ex2(mb - mx), fc = ex2(mc - mx);
        const float inv = rcp(fmaf(fa, os[0], fmaf(fb, os[2], fc * ot[0])));
        fa *= inv; fb *= inv; fc *= inv;
        const uint32_t x = pack2(fmaf(fa, o[0][0], fmaf(fb, o[2][0], fc * o[4][0])), fmaf(fa, o[0][1], fmaf(fb, o[2][1], fc * o[4][1])));
        const uint32_t y = pack2(fmaf(fa, o[1][0], fmaf(fb, o[3][0], fc * o[5][0])), fmaf(fa, o[1][1], fmaf(fb, o[3][1], fc * o[5][1])));
#pragma unroll
        for (int d = 0; d < CL; d++) {
          int r = rank + d; if (r >= CL) r -= CL;
          const uint32_t rb = mapa(sb, r);
          st_async2(rb + OFF_OG + wt * 8 + d * 1024, x, y, rb + OFF_BAR + B_B + 8 * (d >> 1));
        }
        bar_arrive(NB_V, 384);
        if (wt == 0) mbar_expect(bar + B_A, 3 * 1024);
      }
      uint32_t e[5];
      {
        float v[20];
        uint64_t da = mkdesc(sb + OFF_Q, 16, 512, 1), db = mkdesc(sb + OFF_K, 16, 1024, 1);
        OPAQUE64(db); OPAQUE64(da);
        WG_FENCE();
        wg_ss40<0, 0>(v, da, db);
        wg_ss40<1, 0>(v, da + 2, db + 2);
        wg_ss40<1, 0>(v, da + 4, db + 4);
        wg_ss40<1, 0>(v, da + 6, db + 6);
        WG_COMMIT();
        WG_WAIT(0);
#pragma unroll
        for (int i = 0; i < 5; i++) e[i] = pack2(v[4 * i], v[4 * i + 1]);
      }
      if (!last) {
        bar_arrive(NB_TS, 384);
        if (!((w4 == 1 || w4 == 2) && rank < 4)) bar_arrive(NB_G1, 384);
        if (w4 == 3) {
          if ((s & 3) == 0 && s > 0 && lane == 0) { __threadfence(); atomicAdd(&g_flag[(s >> 2) - 1], 1u); }
          __syncwarp();
        } else if (w4 != 0 && rank < 4) {
          if (s == 0) mbar_wait(bar + B_WO, 0);
          const uint32_t kh = w4 - 1, l7 = lane & 7, l3 = lane >> 3;
          const uint32_t wo = sb + OFF_WO + 6 * 12288 + kh * 2048 + ((l3 >> 1) * 8 + l7) * 32 + (((l3 & 1) ^ (l7 >> 2)) << 4);
          const uint32_t og = sb + OFF_OG + kh * 1024 + lane * 8;
          float u[4] = {0.f, 0.f, 0.f, 0.f};
#pragma unroll
          for (int it = 0; it < 3; it++) {
            uint32_t ff[16];
#pragma unroll
            for (int kk = 0; kk < 4; kk++) ldsm4t(ff[4 * kk], ff[4 * kk + 1], ff[4 * kk + 2], ff[4 * kk + 3], wo + it * 4096 + kk * 512);
            mbar_wait(bar + B_B + 8 * it, s & 1);
#pragma unroll
            for (int kk = 0; kk < 4; kk++) {
              const float2 o = lds2f(og + it * 2048 + kk * 256);
              mma16816(u, ff[4 * kk], ff[4 * kk + 1], ff[4 * kk + 2], ff[4 * kk + 3], __float_as_uint(o.x), __float_as_uint(o.y));
            }
          }
          const uint32_t xb = sb + OFF_RA + lane * 8;
          sts2f(xb + kh * 256, kh ? u[0] : u[2], kh ? u[1] : u[3]);
          bar_arrive(NB_G1, 384);
          float4* o = g_acc + (s * ACC_CHUNKS + (2 * rank + kh) * 160 + 128) + lane;
          bar_sync(NB_R + 2, 64);
          const float2 x = lds2f(xb + 256 - kh * 256);
          red4(o, (kh ? u[2] : u[0]) + x.x, (kh ? u[3] : u[1]) + x.y, 0.f, 1.0f);
        }
        bar_sync(NB_G, 384);
        if (wt < 3) mbar_expect(bar + B_B + 8 * wt, 2048);
      } else {
        mbar_wait(bar + B_A, s & 1);
      }
      {
#pragma unroll
        for (int d = 1; d <= 2; d++) {
          const uint32_t rb = mapa(sb, hb + (j3 + d) % 3);
          st_async4(rb + OFF_RT + (2 - d) * 2560 + wt * 16, e[0], e[1], e[2], e[3], rb + OFF_BAR + B_T);
          st_async1(rb + OFF_RT + (2 - d) * 2560 + 2048 + wt * 4, e[4], rb + OFF_BAR + B_T);
        }
      }
      mbar_wait(bar + B_T, s & 1);
      float p[10];
#pragma unroll
      for (int i = 0; i < 5; i++) { p[2 * i] = __uint_as_float(e[i] << 16); p[2 * i + 1] = __uint_as_float(e[i] & 0xffff0000u); }
#pragma unroll
      for (int d = 0; d < 2; d++) {
        const uint4 x = lds4u(sb + OFF_RT + d * 2560 + wt * 16);
        const uint32_t y = __float_as_uint(lds1f(sb + OFF_RT + d * 2560 + 2048 + wt * 4));
        p[0] += __uint_as_float(x.x << 16); p[1] += __uint_as_float(x.x & 0xffff0000u);
        p[2] += __uint_as_float(x.y << 16); p[3] += __uint_as_float(x.y & 0xffff0000u);
        p[4] += __uint_as_float(x.z << 16); p[5] += __uint_as_float(x.z & 0xffff0000u);
        p[6] += __uint_as_float(x.w << 16); p[7] += __uint_as_float(x.w & 0xffff0000u);
        p[8] += __uint_as_float(y << 16); p[9] += __uint_as_float(y & 0xffff0000u);
      }
      if (wt == 0) mbar_expect(bar + B_T, 2 * 2560);
      MemLoad<4> ml;
#pragma unroll
      for (int q = 0; q < 4; q++) ml.c[q] = make_float4(0.f, 0.f, 0.f, 0.f);
      if (!last) memload_issue(ml, s, warp, lane);
      {
        const int tq = 8 * w4 + (lane >> 2) - 2 * (lane & 3);
        float mx = fmaxf(p[8], p[9]);
#pragma unroll
        for (int i = 0; i < 8; i++) { if (8 * (i >> 1) + (i & 1) > tq) p[i] = -INFINITY; mx = fmaxf(mx, p[i]); }
        mx = fmaxf(mx, __shfl_xor_sync(~0u, mx, 1)); mx = fmaxf(mx, __shfl_xor_sync(~0u, mx, 2));
        float sum = 0.f;
#pragma unroll
        for (int i = 0; i < 10; i++) { p[i] = ex2(fmaf(p[i], sc, -mx * sc)); sum += p[i]; }
        sum += __shfl_xor_sync(~0u, sum, 1); sum += __shfl_xor_sync(~0u, sum, 2);
        const float inv = rcp(sum);
        const uint32_t pr = sb + OFF_P + (lane >> 3) * 800 + w4 * 32 + (lane & 7) * 4;
#pragma unroll
        for (int i = 0; i < 5; i++) sts1u(pr + i * 128, pack2(p[2 * i] * inv, p[2 * i + 1] * inv));
        sts1u(pr + 640, 0u);
      }
      if (!last) {
        memload_finish(ml, s, warp, lane, sb, (float)NCL);
        bar_arrive(NB_M, 384);
      }
      fence_async();
      bar_sync(NB_P, 128);
      {
        float o[16];
        uint64_t db = mkdesc(sb + OFF_P, 128, 800, 0);
        OPAQUE64(db);
        uint32_t vb[10];
#pragma unroll
        for (int i = 0; i < 10; i++) asm volatile("add.u32 %0, %1, %2;" : "=r"(vb[i]) : "r"(va[i]), "r"(zero));
        WG_FENCE();
        wg_rs32<0>(o, vb[0], vb[1], vb[2], vb[3], db);
        wg_rs32<1>(o, vb[4], vb[5], vb[6], vb[7], db + 16);
        wg_rs32<1>(o, vb[8], vb[9], 0u, 0u, db + 32);
        WG_COMMIT();
        uint4* dst = reinterpret_cast<uint4*>(g_oT) + ((s * HD + blockIdx.x * 64 + w4 * 16) * 4 + lane);
        WG_WAIT(0);
        dst[0] = make_uint4(pack2(o[0], o[1]), pack2(o[4], o[5]), pack2(o[8], o[9]), pack2(o[12], o[13]));
        dst[32] = make_uint4(pack2(o[2], o[3]), pack2(o[6], o[7]), pack2(o[10], o[11]), pack2(o[14], o[15]));
      }
    }
    bar_sync(NB_P, 128);
    if (tid0 == 256) { __threadfence(); atomicAdd(&g_flag[15], 1u); }
    cluster_sync();
  }
}

namespace hk {
constexpr int STAGES = 4, STAGE = 49152, OFF_ST = STAGES * STAGE, OFF_BAR = OFF_ST + 32768, SMEM = OFF_BAR + 1024, NCTA = NHELP;
constexpr int N_G1 = 192, SB0 = 12  , N_FULL = 5 * SB0, N_ITEMS = N_G1 + 20 + N_FULL + 5 * (2 + 4 + 7) + 1 + 35;
struct Item { int type, mb, nt, k0, k1, nsplit; };
__device__ __forceinline__ Item get_item(int i) {
  Item t;
  if (i < N_G1) { t.type = 0; t.mb = i / 12; t.nt = i % 12; t.k0 = 0; t.k1 = 10; t.nsplit = 1; return t; }
  i -= N_G1; t.type = 1; t.nt = i % 5;
  if (i < 20) { t.mb = SB0 + i / 5; t.k0 = 0; t.k1 = 24; t.nsplit = t.mb == 12 ? 3 : t.mb == 13 ? 5 : 8; return t; }
  i -= 20;
  if (i < N_FULL) { t.mb = i / 5; t.k0 = 0; t.k1 = 120; t.nsplit = 1; return t; }
  i -= N_FULL;
  int ns;
  if (i < 10) { t.mb = 12; ns = 2; } else if (i < 30) { i -= 10; t.mb = 13; ns = 4; } else if (i < 65) { i -= 30; t.mb = 14; ns = 7; }
  else if (i == 65) { t.type = 2; t.mb = t.k0 = t.k1 = 0; t.nsplit = 1; return t; }
  else { i -= 66; t.mb = 15; ns = 7; }
  t.nt = i % 5;
  const int p = i / 5;
  t.k0 = 24 + (96 * p) / ns; t.k1 = 24 + (96 * (p + 1)) / ns; t.nsplit = ns + 1;
  return t;
}
__device__ __forceinline__ void store_tile(const uint32_t* p, uint32_t stg, const CUtensorMap* tm, int c0, int r0, int wg, int t128) {
  const int lane = t128 & 31, r = (t128 >> 5) * 16 + (lane & 15);
  if (t128 == 0) asm volatile("cp.async.bulk.wait_group.read 0;" ::: "memory");
  bar_sync(1 + wg, 128);
#pragma unroll
  for (int j = 0; j < 8; j++) {
    const int c = 2 * j + (lane >> 4);
    const uint32_t a = stg + (c >> 3) * 8192 + r * 128 + (((c & 7) ^ (r & 7)) << 4);
    asm volatile("stmatrix.sync.aligned.m8n8.x4.shared.b16 [%0], {%1,%2,%3,%4};" :: "r"(a), "r"(p[4 * j]), "r"(p[4 * j + 1]), "r"(p[4 * j + 2]), "r"(p[4 * j + 3]) : "memory");
  }
  fence_async();
  bar_sync(1 + wg, 128);
  if (t128 == 0) {
    asm volatile("cp.async.bulk.tensor.2d.global.shared::cta.bulk_group [%0, {%2, %3}], [%1];" :: "l"(tm), "r"(stg), "r"(c0), "r"(r0) : "memory");
    asm volatile("cp.async.bulk.tensor.2d.global.shared::cta.bulk_group [%0, {%2, %3}], [%1];" :: "l"(tm), "r"(stg + 8192), "r"(c0 + 64), "r"(r0) : "memory");
    asm volatile("cp.async.bulk.commit_group;" ::: "memory");
  }
}
}
__global__ void __launch_bounds__(384, 1)
helper_kernel(const __grid_constant__ CUtensorMap tm_x, const __grid_constant__ CUtensorMap tm_g, const __grid_constant__ CUtensorMap tm_u,
              const __grid_constant__ CUtensorMap tm_h, const __grid_constant__ CUtensorMap tm_o, const __grid_constant__ CUtensorMap tm_wd,
              const __grid_constant__ CUtensorMap tm_wo, const __grid_constant__ CUtensorMap tm_hs, const __grid_constant__ CUtensorMap tm_out,
              const bf16* __restrict__ x) {
  using namespace hk;
  extern __shared__ __align__(1024) unsigned char smem[];
  const uint32_t sb = smem_u32(smem), bar = sb + OFF_BAR;
  const int tid = threadIdx.x, lane = tid & 31, wg = __shfl_sync(~0u, tid >> 7, 0);
  if (tid == 0) { for (int i = 0; i < STAGES; i++) { mbar_init(bar + 8 * i, 1); mbar_init(bar + 64 + 8 * i, 2); } asm volatile("fence.mbarrier_init.release.cluster;" ::: "memory"); }
  __syncthreads();
  const int i0 = blockIdx.x;
  if (wg == 2) {
    asm volatile("setmaxnreg.dec.sync.aligned.u32 40;");
    if (tid == 256) {
      uint32_t it = 0;
      wait_flag(&g_flag[F_LN], 96);
      wait_flag(&g_flag[F_W], 48);
      for (int i = i0; i < N_ITEMS; i += NCTA) {
        const Item t = get_item(i);
        const int m0 = t.mb * 128, n0 = t.nt * 128;
        int kb = t.k0;
        if (t.type == 1 && kb == 0) wait_flag(&g_flag[16 + t.mb], 24);
        for (; kb < t.k1 && kb < 24; kb++, it++) {
          const uint32_t st = it % STAGES, base = sb + st * STAGE, full = bar + 8 * st;
          mbar_wait_long(bar + 64 + 8 * st, ((it / STAGES) & 1) ^ 1);
          if (t.type == 0) {
            mbar_expect(full, 49152);
            tma2d(base, &tm_x, kb * 64, m0, full);
            tma2d(base + 16384, &tm_g, n0, kb * 64, full);
            tma2d(base + 24576, &tm_g, n0 + 64, kb * 64, full);
            tma2d(base + 32768, &tm_u, n0, kb * 64, full);
            tma2d(base + 40960, &tm_u, n0 + 64, kb * 64, full);
          } else {
            mbar_expect(full, 32768);
            tma2d(base, &tm_h, kb * 64, m0, full);
            tma2d(base + 16384, &tm_wd, n0, kb * 64, full);
            tma2d(base + 24576, &tm_wd, n0 + 64, kb * 64, full);
          }
        }
        const int kf = kb;
        for (; kb < t.k1; kb++, it++) {
          const uint32_t st = it % STAGES, base = sb + st * STAGE, full = bar + 8 * st;
          const int k0 = (kb - 24) * 64;
          mbar_wait_long(bar + 64 + 8 * st, ((it / STAGES) & 1) ^ 1);
          mbar_expect(full, 32768);
          tma2d(base + 16384, &tm_wo, n0, k0, full);
          tma2d(base + 24576, &tm_wo, n0 + 64, k0, full);
          if (kb == kf + STAGES - 2) {
            wait_flag(&g_flag[t.mb], 96);
            for (int j = STAGES - 2; j > 0; j--) tma3d(sb + ((it - j) % STAGES) * STAGE, &tm_o, 0, k0 - j * 64, m0 / 32, bar + 8 * ((it - j) % STAGES));
          }
          if (kb >= kf + STAGES - 2) tma3d(base, &tm_o, 0, k0, m0 / 32, full);
        }
      }
    }
  } else {
    asm volatile("setmaxnreg.inc.sync.aligned.u32 232;");
    uint32_t it = 0;
    for (int i = i0; i < N_ITEMS; i += NCTA) {
      const Item t = get_item(i);
      const int row = t.mb * 128 + wg * 64 + ((tid >> 5) & 3) * 16 + (lane >> 2);
      if (t.type == 2) continue;
      if (t.type == 0) {
        float dg[64], du[64];
#pragma unroll
        for (int j = 0; j < 64; j++) { dg[j] = 0.f; du[j] = 0.f; }
        for (int kb = 0; kb < 10; kb++, it++) {
          const uint32_t st = it % STAGES, base = sb + st * STAGE;
          mbar_wait_long(bar + 8 * st, (it / STAGES) & 1);
          const uint64_t da = mkdesc(base + wg * 8192, 16, 1024, 1), db = mkdesc(base + 16384, 8192, 1024, 1);
          WG_FENCE();
#pragma unroll
          for (int k = 0; k < 4; k++) { wg_ss128<0>(dg, da + 2 * k, db + 128 * k); wg_ss128<0>(du, da + 2 * k, db + 1024 + 128 * k); }
          WG_COMMIT();
          WG_WAIT(1);
          if (kb > 0 && (tid & 127) == 0) mbar_arrive(bar + 64 + 8 * ((it - 1) % STAGES));
        }
        WG_WAIT(0);
        if ((tid & 127) == 0) mbar_arrive(bar + 64 + 8 * ((it - 1) % STAGES));
        uint32_t p[32];
#pragma unroll
        for (int j = 0; j < 32; j++) p[j] = pack2(bfr(dg[2 * j]) * bfr(du[2 * j]), bfr(dg[2 * j + 1]) * bfr(du[2 * j + 1]));
        store_tile(p, sb + OFF_ST + wg * 16384, &tm_hs, t.nt * 128, t.mb * 128 + wg * 64, wg, tid & 127);
        if ((tid & 127) == 0) {
          asm volatile("cp.async.bulk.wait_group 0;" ::: "memory");
          asm volatile("fence.proxy.async;" ::: "memory");
          __threadfence(); atomicAdd(&g_flag[16 + t.mb], 1u);
        }
      } else {
        float d[64];
#pragma unroll
        for (int j = 0; j < 64; j++) d[j] = 0.f;
        uint32_t xr[32];
        {
          const uint32_t* xi = reinterpret_cast<const uint32_t*>(x + (size_t)row * DM + t.nt * 128 + (lane & 3) * 2);
#pragma unroll
          for (int j = 0; j < 16; j++) { xr[2 * j] = __ldg(xi + j * 4); xr[2 * j + 1] = __ldg(xi + j * 4 + 4 * DM); }
        }
        int kb = t.k0;
        for (; kb < t.k1 && kb < 24; kb++, it++) {
          const uint32_t st = it % STAGES, base = sb + st * STAGE;
          mbar_wait_long(bar + 8 * st, (it / STAGES) & 1);
          const uint64_t da = mkdesc(base + wg * 8192, 16, 1024, 1), db = mkdesc(base + 16384, 8192, 1024, 1);
          WG_FENCE();
#pragma unroll
          for (int k = 0; k < 4; k++) wg_ss128<0>(d, da + 2 * k, db + 128 * k);
          WG_COMMIT();
          WG_WAIT(1);
          if (kb > t.k0 && (tid & 127) == 0) mbar_arrive(bar + 64 + 8 * ((it - 1) % STAGES));
        }
        WG_WAIT(0);
        for (; kb < t.k1; kb++, it++) {
          const uint32_t st = it % STAGES, base = sb + st * STAGE;
          mbar_wait_long(bar + 8 * st, (it / STAGES) & 1);
          const uint64_t da = mkdesc(base + wg * 8192, 4096, 512, 2), db = mkdesc(base + 16384, 8192, 1024, 1);
          WG_FENCE();
#pragma unroll
          for (int k = 0; k < 4; k++) wg_ss128<1>(d, da + 64 * k, db + 128 * k);
          WG_COMMIT();
          WG_WAIT(1);
          if (kb > t.k0 && (tid & 127) == 0) mbar_arrive(bar + 64 + 8 * ((it - 1) % STAGES));
        }
        WG_WAIT(0);
        if ((tid & 127) == 0) mbar_arrive(bar + 64 + 8 * ((it - 1) % STAGES));
        {
          const uint32_t m = t.k0 == 0 ? 0xffff0000u : 0u;
#pragma unroll
          for (int j = 0; j < 32; j++) { d[2 * j] += __uint_as_float((xr[j] << 16) & m); d[2 * j + 1] += __uint_as_float(xr[j] & m); }
        }
        bool fin = true;
        if (t.nsplit > 1) {
          const int ti = (t.mb - SB0) * 5 + t.nt;
          float4* pp = g_part + ti * 4096 + tid;
#pragma unroll
          for (int j = 0; j < 16; j++) red4(pp + j * 256, d[4 * j], d[4 * j + 1], d[4 * j + 2], d[4 * j + 3]);
          bar_sync(1 + wg, 128);
          volatile unsigned* sflag = reinterpret_cast<volatile unsigned*>(smem + OFF_BAR + 256 + wg * 4);
          if ((tid & 127) == 0) {
            __threadfence();
            const unsigned old = atomicAdd(&g_flag[32 + ti], wg ? 0x10000u : 1u);
            *sflag = ((wg ? old >> 16 : old & 0xffffu) == (unsigned)t.nsplit - 1);
            __threadfence();
          }
          bar_sync(1 + wg, 128);
          fin = __shfl_sync(~0u, *sflag, 0) != 0;
          if (fin) {
#pragma unroll
            for (int j = 0; j < 16; j++) {
              const float4 u = __ldcg(pp + j * 256);
              d[4 * j] = u.x; d[4 * j + 1] = u.y; d[4 * j + 2] = u.z; d[4 * j + 3] = u.w;
            }
          }
        }
        if (fin) {
          uint32_t p[32];
#pragma unroll
          for (int j = 0; j < 32; j++) p[j] = pack2(d[2 * j], d[2 * j + 1]);
          store_tile(p, sb + OFF_ST + wg * 16384, &tm_out, t.nt * 128, t.mb * 128 + wg * 64, wg, tid & 127);
        }
      }
    }
    bar_sync(3, 256);
    if (tid >= 32 && tid < 64) {
      asm volatile("griddepcontrol.wait;" ::: "memory");
      unsigned old = 0;
      if (lane == 0) old = atomicAdd(&g_flag[F_DONE], 1u);
      if (__shfl_sync(~0u, old, 0) == NCTA - 1) { g_flag[lane] = 0; g_flag[32 + lane] = 0; }
    }
    if ((tid & 127) == 0) asm volatile("cp.async.bulk.wait_group 0;" ::: "memory");
  }
}

__global__ void fb_ln(const bf16* __restrict__ x) {
  uint2 u[5];
  const int row = blockIdx.x * 8 + (threadIdx.x >> 5), lane = threadIdx.x & 31;
  for (int j = 0; j < 5; j++) u[j] = reinterpret_cast<const uint2*>(x + (size_t)row * DM)[j * 32 + lane];
  ln_row(u, row, lane);
}
__global__ void fb_gemm(const bf16* A0, const bf16* A1, int m_split, const bf16* B, bf16* C0, bf16* C1, int N, int K, int mode, const bf16* R0, const bf16* R1) {
  const int n = blockIdx.x * blockDim.x + threadIdx.x, m = blockIdx.y;
  const bf16* a = m < m_split ? A0 + (size_t)m * K : A1 + (size_t)(m - m_split) * K;
  bf16* c = (m < m_split ? C0 + (size_t)m * N : C1 + (size_t)(m - m_split) * N) + n;
  float acc = 0.f;
  for (int k = 0; k < K; k++) acc += __bfloat162float(a[k]) * __bfloat162float(B[(size_t)k * N + n]);
  if (mode == 1) acc = bfr(acc) * __bfloat162float(*c);
  if (mode == 2) acc += __bfloat162float(R0[(size_t)m * N + n]) + __bfloat162float(R1[(size_t)m * N + n]);
  *c = __float2bfloat16_rn(acc);
}
__global__ void fb_attn(const bf16* q, const bf16* k, const bf16* v, bf16* o) {
  const int h = blockIdx.x, r = blockIdx.y, t = threadIdx.x;
  __shared__ float p[40];
  if (t < 40) {
    float a = 0.f;
    for (int e = 0; e < 192; e++) a += __bfloat162float(q[r * HD + h * 192 + e]) * __bfloat162float(k[t * HD + h * 192 + e]);
    p[t] = (r < 8 || r >= t) ? a * 0.07216878364870322f : -INFINITY;
  }
  __syncthreads();
  float mx = p[0], sum = 0.f, a = 0.f;
  for (int i = 1; i < 40; i++) mx = fmaxf(mx, p[i]);
  for (int i = 0; i < 40; i++) sum += __expf(p[i] - mx);
  for (int i = 0; i < 40; i++) a += bfr(__expf(p[i] - mx) / sum) * __bfloat162float(v[i * HD + h * 192 + t]);
  o[r * HD + h * 192 + t] = __float2bfloat16_rn(a);
}

typedef CUresult (*EncodeFn)(CUtensorMap*, CUtensorMapDataType, cuuint32_t, void*, const cuuint64_t*, const cuuint64_t*, const cuuint32_t*,
                             const cuuint32_t*, CUtensorMapInterleave, CUtensorMapSwizzle, CUtensorMapL2promotion, CUtensorMapFloatOOBfill);
static void make_map(EncodeFn enc, CUtensorMap* m, const void* p, int rank, const cuuint64_t* dims, const cuuint64_t* strides,
                     const cuuint32_t* box, CUtensorMapSwizzle swz) {
  cuuint32_t es[3] = {1, 1, 1};
  enc(m, CU_TENSOR_MAP_DATA_TYPE_BFLOAT16, rank, const_cast<void*>(p), dims, strides, box, es, CU_TENSOR_MAP_INTERLEAVE_NONE, swz,
      CU_TENSOR_MAP_L2_PROMOTION_L2_128B, CU_TENSOR_MAP_FLOAT_OOB_FILL_NONE);
}
static void map2d(EncodeFn enc, CUtensorMap* m, const void* p, int cols, int rows, int bc, int br, CUtensorMapSwizzle swz) {
  cuuint64_t dims[2] = {(cuuint64_t)cols, (cuuint64_t)rows}, strides[1] = {(cuuint64_t)cols * 2};
  cuuint32_t box[2] = {(cuuint32_t)bc, (cuuint32_t)br};
  make_map(enc, m, p, 2, dims, strides, box, swz);
}

extern "C" void kernel_launch(void* const* d_in, const int* in_sizes, int n_in, void* d_out, int out_size) {
  const bf16* x = (const bf16*)d_in[0];
  const bf16* mem0 = (const bf16*)d_in[1];
  const bf16* Wq = (const bf16*)d_in[2];
  const bf16* Wk = (const bf16*)d_in[3];
  const bf16* Wv = (const bf16*)d_in[4];
  const bf16* Wo = (const bf16*)d_in[5];
  const bf16* Wg = (const bf16*)d_in[8];
  const bf16* Wu = (const bf16*)d_in[9];
  const bf16* Wd = (const bf16*)d_in[10];
  bf16* out = (bf16*)d_out;

  void* fn = nullptr; cudaDriverEntryPointQueryResult qr;
  cudaGetDriverEntryPoint("cuTensorMapEncodeTiled", &fn, cudaEnableDefault, &qr);
  EncodeFn enc = (EncodeFn)fn;
  void *p_xn, *p_oT, *p_h;
  cudaGetSymbolAddress(&p_xn, g_xn); cudaGetSymbolAddress(&p_oT, g_oT); cudaGetSymbolAddress(&p_h, g_h);

  CUtensorMap t_x32, t_wv, t_wo16, t_x128, t_wg, t_wu, t_h, t_o, t_wd, t_wo64, t_hs, t_out, t_wq, t_wk;
  map2d(enc, &t_wq, Wq, HD, DM, 64, 128, CU_TENSOR_MAP_SWIZZLE_128B);
  map2d(enc, &t_wk, Wk, HD, DM, 64, 128, CU_TENSOR_MAP_SWIZZLE_128B);
  map2d(enc, &t_hs, p_h, FF, SEQ, 64, 64, CU_TENSOR_MAP_SWIZZLE_128B);
  map2d(enc, &t_out, out, DM, SEQ, 64, 64, CU_TENSOR_MAP_SWIZZLE_128B);
  map2d(enc, &t_x32, p_xn, DM, SEQ, 64, 32, CU_TENSOR_MAP_SWIZZLE_128B);
  map2d(enc, &t_wv, Wv, HD, DM, 64, 128, CU_TENSOR_MAP_SWIZZLE_128B);
  map2d(enc, &t_wo16, Wo, DM, HD, 16, 64, CU_TENSOR_MAP_SWIZZLE_32B);
  map2d(enc, &t_x128, p_xn, DM, SEQ, 64, 128, CU_TENSOR_MAP_SWIZZLE_128B);
  map2d(enc, &t_wg, Wg, FF, DM, 64, 64, CU_TENSOR_MAP_SWIZZLE_128B);
  map2d(enc, &t_wu, Wu, FF, DM, 64, 64, CU_TENSOR_MAP_SWIZZLE_128B);
  map2d(enc, &t_h, p_h, FF, SEQ, 64, 128, CU_TENSOR_MAP_SWIZZLE_128B);
  map2d(enc, &t_wd, Wd, DM, FF, 64, 64, CU_TENSOR_MAP_SWIZZLE_128B);
  map2d(enc, &t_wo64, Wo, DM, HD, 64, 64, CU_TENSOR_MAP_SWIZZLE_128B);
  {
    cuuint64_t dims[3] = {32, (cuuint64_t)HD, (cuuint64_t)NSEG}, strides[2] = {64, (cuuint64_t)HD * 64};
    cuuint32_t box[3] = {32, 64, 4};
    make_map(enc, &t_o, p_oT, 3, dims, strides, box, CU_TENSOR_MAP_SWIZZLE_64B);
  }
  cudaFuncSetAttribute(chain_kernel, cudaFuncAttributeMaxDynamicSharedMemorySize, ck::SMEM);
  cudaFuncSetAttribute(helper_kernel, cudaFuncAttributeMaxDynamicSharedMemorySize, hk::SMEM);

  cudaStream_t st = cudaStreamPerThread;
  {
    cudaLaunchConfig_t cfg = {};
    cfg.gridDim = dim3(ck::CL * ck::NCL); cfg.blockDim = dim3(384); cfg.dynamicSmemBytes = ck::SMEM; cfg.stream = st;
    cudaLaunchAttribute at[1];
    at[0].id = cudaLaunchAttributeClusterDimension; at[0].val.clusterDim.x = ck::CL; at[0].val.clusterDim.y = 1; at[0].val.clusterDim.z = 1;
    cfg.attrs = at; cfg.numAttrs = 1;
    int ncl = 0;
    if (cudaOccupancyMaxActiveClusters(&ncl, chain_kernel, &cfg) != cudaSuccess) { (void)cudaGetLastError(); ncl = 0; }
    if (ncl < ck::NCL) {
      bf16 *xn = (bf16*)p_xn, *h = (bf16*)p_h, *q = (bf16*)p_oT, *k = q + 40 * HD, *v = k + 40 * HD, *o = v + 40 * HD, *mem = o + 40 * HD, *att = mem + 8 * DM;
      fb_ln<<<SEQ / 8, 256, 0, st>>>(x);
      for (int s = 0; s < NSEG; s++) {
        const bf16 *m = s ? mem : mem0, *xs = xn + s * 32 * DM;
        fb_gemm<<<dim3(HD / 128, 40), 128, 0, st>>>(m, xs, 8, Wq, q, q + 8 * HD, HD, DM, 0, nullptr, nullptr);
        fb_gemm<<<dim3(HD / 128, 40), 128, 0, st>>>(m, xs, 8, Wk, k, k + 8 * HD, HD, DM, 0, nullptr, nullptr);
        fb_gemm<<<dim3(HD / 128, 40), 128, 0, st>>>(m, xs, 8, Wv, v, v + 8 * HD, HD, DM, 0, nullptr, nullptr);
        fb_attn<<<dim3(32, 40), 192, 0, st>>>(q, k, v, o);
        fb_gemm<<<dim3(DM / 128, 40), 128, 0, st>>>(o, o + 8 * HD, 8, Wo, mem, att + s * 32 * DM, DM, HD, 0, nullptr, nullptr);
      }
      fb_gemm<<<dim3(FF / 128, SEQ), 128, 0, st>>>(xn, xn, SEQ, Wg, h, h, FF, DM, 0, nullptr, nullptr);
      fb_gemm<<<dim3(FF / 128, SEQ), 128, 0, st>>>(xn, xn, SEQ, Wu, h, h, FF, DM, 1, nullptr, nullptr);
      fb_gemm<<<dim3(DM / 128, SEQ), 128, 0, st>>>(h, h, SEQ, Wd, out, out, DM, FF, 2, x, att);
      return;
    }
    cudaLaunchKernelEx(&cfg, chain_kernel, t_x32, t_wv, t_wo16, t_wq, t_wk, mem0, x, 0u);
  }
  {
    cudaLaunchConfig_t cfg = {};
    cfg.gridDim = dim3(hk::NCTA); cfg.blockDim = dim3(384); cfg.dynamicSmemBytes = hk::SMEM; cfg.stream = st;
    cudaLaunchAttribute at[1];
    at[0].id = cudaLaunchAttributeProgrammaticStreamSerialization; at[0].val.programmaticStreamSerializationAllowed = 1;
    cfg.attrs = at; cfg.numAttrs = 1;
    cudaLaunchKernelEx(&cfg, helper_kernel, t_x128, t_wg, t_wu, t_h, t_o, t_wd, t_wo64, t_hs, t_out, x);
  }
}
```

```cpp
#include <cuda_runtime.h>
#include <cuda_bf16.h>
#include <cuda.h>
#include <stdint.h>

typedef __nv_bfloat16 bf16;

constexpr int SEQ = 2048, DM = 640, HD = 6144, FF = 1536, NSEG = 64;
constexpr int ACC_CHUNKS = 1920;

__device__ __align__(1024) bf16 g_xn[SEQ * DM];
__device__ __align__(1024) bf16 g_oT[NSEG * HD * 32];
__device__ __align__(1024) bf16 g_h[SEQ * FF];
__device__ __align__(1024) float4 g_acc[NSEG * ACC_CHUNKS];
__device__ __align__(1024) float4 g_part[20 * 4096];
__device__ unsigned g_flag[64];

__device__ __forceinline__ uint32_t smem_u32(const void* p) { return (uint32_t)__cvta_generic_to_shared(p); }
__device__ __forceinline__ uint32_t mapa(uint32_t a, uint32_t r) { uint32_t o; asm("mapa.shared::cluster.u32 %0, %1, %2;" : "=r"(o) : "r"(a), "r"(r)); return o; }
__device__ __forceinline__ void mbar_init(uint32_t b, int c) { asm volatile("mbarrier.init.shared::cta.b64 [%0], %1;" :: "r"(b), "r"(c) : "memory"); }
__device__ __forceinline__ void mbar_expect(uint32_t b, uint32_t bytes) { asm volatile("mbarrier.arrive.expect_tx.shared::cta.b64 _, [%0], %1;" :: "r"(b), "r"(bytes) : "memory"); }
__device__ __forceinline__ void mbar_arrive(uint32_t b) { asm volatile("mbarrier.arrive.shared::cta.b64 _, [%0];" :: "r"(b) : "memory"); }
constexpr int SPIN_LIMIT = 1 << 20;
__device__ __forceinline__ void mbar_wait(uint32_t b, uint32_t ph) {
  asm volatile("{\n.reg .pred p;\n.reg .u32 n;\nmov.u32 n, 0;\n"
               "W: mbarrier.try_wait.parity.shared::cta.b64 p, [%0], %1;\n@p bra D;\n"
               "add.u32 n, n, 1;\nsetp.lt.u32 p, n, 0x40000;\n@p bra W;\ntrap;\nD:\n}" :: "r"(b), "r"(ph) : "memory");
}
__device__ __forceinline__ void mbar_wait_long(uint32_t b, uint32_t ph) {
  asm volatile("{\n.reg .pred p;\n.reg .u32 n;\nmov.u32 n, 0;\n"
               "W: mbarrier.try_wait.parity.shared::cta.b64 p, [%0], %1;\n@p bra D;\n"
               "add.u32 n, n, 1;\nsetp.lt.u32 p, n, 0x400000;\n@p bra W;\ntrap;\nD:\n}" :: "r"(b), "r"(ph) : "memory");
}
__device__ __forceinline__ void bar_sync(int id, int n) { asm volatile("bar.sync %0, %1;" :: "r"(id), "r"(n) : "memory"); }
__device__ __forceinline__ void bar_arrive(int id, int n) { asm volatile("bar.arrive %0, %1;" :: "r"(id), "r"(n) : "memory"); }
__device__ __forceinline__ void fence_async() { asm volatile("fence.proxy.async.shared::cta;" ::: "memory"); }
__device__ __forceinline__ void cluster_sync() { asm volatile("barrier.cluster.arrive.release.aligned;\nbarrier.cluster.wait.acquire.aligned;" ::: "memory"); }
__device__ __forceinline__ void tma2d(uint32_t dst, const CUtensorMap* m, int c0, int c1, uint32_t bar) {
  asm volatile("cp.async.bulk.tensor.2d.shared::cluster.global.mbarrier::complete_tx::bytes [%0], [%1, {%3, %4}], [%2];"
               :: "r"(dst), "l"(m), "r"(bar), "r"(c0), "r"(c1) : "memory");
}
__device__ __forceinline__ void tma2d_mc(uint32_t dst, const CUtensorMap* m, int c0, int c1, uint32_t bar, uint16_t mask) {
  asm volatile("cp.async.bulk.tensor.2d.shared::cluster.global.mbarrier::complete_tx::bytes.multicast::cluster [%0], [%1, {%3, %4}], [%2], %5;"
               :: "r"(dst), "l"(m), "r"(bar), "r"(c0), "r"(c1), "h"(mask) : "memory");
}
__device__ __forceinline__ void tma3d(uint32_t dst, const CUtensorMap* m, int c0, int c1, int c2, uint32_t bar) {
  asm volatile("cp.async.bulk.tensor.3d.shared::cluster.global.mbarrier::complete_tx::bytes [%0], [%1, {%3, %4, %5}], [%2];"
               :: "r"(dst), "l"(m), "r"(bar), "r"(c0), "r"(c1), "r"(c2) : "memory");
}
__device__ __forceinline__ void st_async1(uint32_t a, uint32_t x, uint32_t mb) {
  asm volatile("st.async.weak.shared::cluster.mbarrier::complete_tx::bytes.b32 [%0], %1, [%2];" :: "r"(a), "r"(x), "r"(mb) : "memory");
}
__device__ __forceinline__ void st_async2(uint32_t a, uint32_t x, uint32_t y, uint32_t mb) {
  asm volatile("st.async.weak.shared::cluster.mbarrier::complete_tx::bytes.v2.b32 [%0], {%1,%2}, [%3];" :: "r"(a), "r"(x), "r"(y), "r"(mb) : "memory");
}
__device__ __forceinline__ void st_async4(uint32_t a, uint32_t x, uint32_t y, uint32_t z, uint32_t w, uint32_t mb) {
  asm volatile("st.async.weak.shared::cluster.mbarrier::complete_tx::bytes.v4.b32 [%0], {%1,%2,%3,%4}, [%5];" :: "r"(a), "r"(x), "r"(y), "r"(z), "r"(w), "r"(mb) : "memory");
}
__device__ __forceinline__ void ldsm4(uint32_t& r0, uint32_t& r1, uint32_t& r2, uint32_t& r3, uint32_t a) {
  asm volatile("ldmatrix.sync.aligned.m8n8.x4.shared.b16 {%0,%1,%2,%3}, [%4];" : "=r"(r0), "=r"(r1), "=r"(r2), "=r"(r3) : "r"(a) : "memory");
}
__device__ __forceinline__ void ldsm4t(uint32_t& r0, uint32_t& r1, uint32_t& r2, uint32_t& r3, uint32_t a) {
  asm volatile("ldmatrix.sync.aligned.m8n8.x4.trans.shared.b16 {%0,%1,%2,%3}, [%4];" : "=r"(r0), "=r"(r1), "=r"(r2), "=r"(r3) : "r"(a) : "memory");
}
__device__ __forceinline__ void stsm4t(uint32_t a, uint32_t r0, uint32_t r1, uint32_t r2, uint32_t r3) {
  asm volatile("stmatrix.sync.aligned.m8n8.x4.trans.shared.b16 [%0], {%1,%2,%3,%4};" :: "r"(a), "r"(r0), "r"(r1), "r"(r2), "r"(r3) : "memory");
}
__device__ __forceinline__ void stsm1t(uint32_t a, uint32_t r0) {
  asm volatile("stmatrix.sync.aligned.m8n8.x1.trans.shared.b16 [%0], {%1};" :: "r"(a), "r"(r0) : "memory");
}
__device__ __forceinline__ void stsm2t(uint32_t a, uint32_t r0, uint32_t r1) {
  asm volatile("stmatrix.sync.aligned.m8n8.x2.trans.shared.b16 [%0], {%1,%2};" :: "r"(a), "r"(r0), "r"(r1) : "memory");
}
__device__ __forceinline__ void mma16816(float* d, uint32_t a0, uint32_t a1, uint32_t a2, uint32_t a3, uint32_t b0, uint32_t b1) {
  asm volatile("mma.sync.aligned.m16n8k16.row.col.f32.bf16.bf16.f32 {%0,%1,%2,%3}, {%4,%5,%6,%7}, {%8,%9}, {%0,%1,%2,%3};"
               : "+f"(d[0]), "+f"(d[1]), "+f"(d[2]), "+f"(d[3]) : "r"(a0), "r"(a1), "r"(a2), "r"(a3), "r"(b0), "r"(b1));
}
__device__ __forceinline__ void mma1688(float* d, uint32_t a0, uint32_t a1, uint32_t b0) {
  asm volatile("mma.sync.aligned.m16n8k8.row.col.f32.bf16.bf16.f32 {%0,%1,%2,%3}, {%4,%5}, {%6}, {%0,%1,%2,%3};"
               : "+f"(d[0]), "+f"(d[1]), "+f"(d[2]), "+f"(d[3]) : "r"(a0), "r"(a1), "r"(b0));
}
__device__ __forceinline__ float ex2(float x) { float r; asm("ex2.approx.ftz.f32 %0, %1;" : "=f"(r) : "f"(x)); return r; }
__device__ __forceinline__ float rcp(float x) { float r; asm("rcp.approx.ftz.f32 %0, %1;" : "=f"(r) : "f"(x)); return r; }
__device__ __forceinline__ uint32_t pack2(float lo, float hi) { uint32_t r; asm("cvt.rn.bf16x2.f32 %0, %1, %2;" : "=r"(r) : "f"(hi), "f"(lo)); return r; }
__device__ __forceinline__ float2 lds2f(uint32_t a) { float2 v; asm volatile("ld.shared.v2.f32 {%0,%1}, [%2];" : "=f"(v.x), "=f"(v.y) : "r"(a) : "memory"); return v; }
__device__ __forceinline__ float4 lds4f(uint32_t a) { float4 v; asm volatile("ld.shared.v4.f32 {%0,%1,%2,%3}, [%4];" : "=f"(v.x), "=f"(v.y), "=f"(v.z), "=f"(v.w) : "r"(a) : "memory"); return v; }
__device__ __forceinline__ uint4 lds4u(uint32_t a) { uint4 v; asm volatile("ld.shared.v4.u32 {%0,%1,%2,%3}, [%4];" : "=r"(v.x), "=r"(v.y), "=r"(v.z), "=r"(v.w) : "r"(a) : "memory"); return v; }
__device__ __forceinline__ float lds1f(uint32_t a) { float v; asm volatile("ld.shared.f32 %0, [%1];" : "=f"(v) : "r"(a) : "memory"); return v; }
__device__ __forceinline__ void sts4f(uint32_t a, float x, float y, float z, float w) { asm volatile("st.shared.v4.f32 [%0], {%1,%2,%3,%4};" :: "r"(a), "f"(x), "f"(y), "f"(z), "f"(w) : "memory"); }
__device__ __forceinline__ void sts2f(uint32_t a, float x, float y) { asm volatile("st.shared.v2.f32 [%0], {%1,%2};" :: "r"(a), "f"(x), "f"(y) : "memory"); }
__device__ __forceinline__ void sts1f(uint32_t a, float x) { asm volatile("st.shared.f32 [%0], %1;" :: "r"(a), "f"(x) : "memory"); }
__device__ __forceinline__ void sts1u(uint32_t a, uint32_t x) { asm volatile("st.shared.u32 [%0], %1;" :: "r"(a), "r"(x) : "memory"); }
__device__ __forceinline__ void sts4u(uint32_t a, uint4 v) { asm volatile("st.shared.v4.u32 [%0], {%1,%2,%3,%4};" :: "r"(a), "r"(v.x), "r"(v.y), "r"(v.z), "r"(v.w) : "memory"); }
__device__ __forceinline__ float4 ld_relaxed4(const float4* p) {
  float4 r; asm volatile("ld.relaxed.gpu.global.v4.f32 {%0,%1,%2,%3}, [%4];" : "=f"(r.x), "=f"(r.y), "=f"(r.z), "=f"(r.w) : "l"(p) : "memory"); return r;
}
__device__ __forceinline__ void red4(float4* p, float a, float b, float c, float d) {
  asm volatile("red.relaxed.gpu.global.add.v4.f32 [%0], {%1,%2,%3,%4};" :: "l"(p), "f"(a), "f"(b), "f"(c), "f"(d) : "memory");
}
__device__ __forceinline__ uint64_t mkdesc(uint32_t addr, uint32_t lbo, uint32_t sbo, uint32_t swz) {
  return (uint64_t)((addr & 0x3FFFF) >> 4) | ((uint64_t)(lbo >> 4) << 16) | ((uint64_t)(sbo >> 4) << 32) | ((uint64_t)swz << 62);
}
#define WG_FENCE() asm volatile("wgmma.fence.sync.aligned;" ::: "memory")
#define WG_COMMIT() asm volatile("wgmma.commit_group.sync.aligned;" ::: "memory")
#define WG_WAIT(n) asm volatile("wgmma.wait_group.sync.aligned %0;" :: "n"(n) : "memory")
#define OPAQUE64(x) asm volatile("" : "+l"(x))

#define F4(d, i) "+f"(d[i]), "+f"(d[i + 1]), "+f"(d[i + 2]), "+f"(d[i + 3])
#define F16(d, i) F4(d, i), F4(d, i + 4), F4(d, i + 8), F4(d, i + 12)
template <int ACC>
__device__ __forceinline__ void wg_rs32(float* d, uint32_t a0, uint32_t a1, uint32_t a2, uint32_t a3, uint64_t b) {
  asm volatile("wgmma.mma_async.sync.aligned.m64n32k16.f32.bf16.bf16 {%0,%1,%2,%3,%4,%5,%6,%7,%8,%9,%10,%11,%12,%13,%14,%15}, {%16,%17,%18,%19}, %20, %21, 1, 1, 0;"
               : F16(d, 0) : "r"(a0), "r"(a1), "r"(a2), "r"(a3), "l"(b), "n"(ACC));
}
template <int ACC>
__device__ __forceinline__ void wg_rs32x(float* d, uint32_t a0, uint32_t a1, uint32_t a2, uint32_t a3, uint32_t blo) {
  asm volatile("{\n.reg .b64 b;\nmov.b64 b, {%20, 0x40000040};\n"
               "wgmma.mma_async.sync.aligned.m64n32k16.f32.bf16.bf16 {%0,%1,%2,%3,%4,%5,%6,%7,%8,%9,%10,%11,%12,%13,%14,%15}, {%16,%17,%18,%19}, b, %21, 1, 1, 0;\n}"
               : F16(d, 0) : "r"(a0), "r"(a1), "r"(a2), "r"(a3), "r"(blo), "n"(ACC));
}
template <int ACC>
__device__ __forceinline__ void wg_rs40(float* d, uint32_t a0, uint32_t a1, uint32_t a2, uint32_t a3, uint64_t b) {
  asm volatile("wgmma.mma_async.sync.aligned.m64n40k16.f32.bf16.bf16 {%0,%1,%2,%3,%4,%5,%6,%7,%8,%9,%10,%11,%12,%13,%14,%15,%16,%17,%18,%19}, {%20,%21,%22,%23}, %24, %25, 1, 1, 0;"
               : F16(d, 0), F4(d, 16) : "r"(a0), "r"(a1), "r"(a2), "r"(a3), "l"(b), "n"(ACC));
}
template <int ACC>
__device__ __forceinline__ void wg_ss8(float* d, uint64_t a, uint64_t b) {
  asm volatile("wgmma.mma_async.sync.aligned.m64n8k16.f32.bf16.bf16 {%0,%1,%2,%3}, %4, %5, %6, 1, 1, 0, 0;" : F4(d, 0) : "l"(a), "l"(b), "n"(ACC));
}
template <int ACC, int TA>
__device__ __forceinline__ void wg_ss40(float* d, uint64_t a, uint64_t b) {
  asm volatile("wgmma.mma_async.sync.aligned.m64n40k16.f32.bf16.bf16 {%0,%1,%2,%3,%4,%5,%6,%7,%8,%9,%10,%11,%12,%13,%14,%15,%16,%17,%18,%19}, %20, %21, %22, 1, 1, %23, 0;"
               : F16(d, 0), F4(d, 16) : "l"(a), "l"(b), "n"(ACC), "n"(TA));
}
template <int TA>
__device__ __forceinline__ void wg_ss128(float* d, uint64_t a, uint64_t b) {
  asm volatile("wgmma.mma_async.sync.aligned.m64n128k16.f32.bf16.bf16 {"
               "%0,%1,%2,%3,%4,%5,%6,%7,%8,%9,%10,%11,%12,%13,%14,%15,%16,%17,%18,%19,%20,%21,%22,%23,%24,%25,%26,%27,%28,%29,%30,%31,"
               "%32,%33,%34,%35,%36,%37,%38,%39,%40,%41,%42,%43,%44,%45,%46,%47,%48,%49,%50,%51,%52,%53,%54,%55,%56,%57,%58,%59,%60,%61,%62,%63"
               "}, %64, %65, 1, 1, 1, %66, 1;"
               : F16(d, 0), F16(d, 16), F16(d, 32), F16(d, 48) : "l"(a), "l"(b), "n"(TA));
}

__device__ __forceinline__ float bfr(float x) { return __bfloat162float(__float2bfloat16_rn(x)); }
constexpr int F_LN = 52, F_DONE = 53, F_W = 54, NHELP = 36;
__device__ __forceinline__ void ln_row(const uint2 (&u)[5], int row, int lane) {
  float v[20];
#pragma unroll
  for (int i = 0; i < 5; i++) {
    v[4 * i + 0] = __uint_as_float(u[i].x << 16); v[4 * i + 1] = __uint_as_float(u[i].x & 0xffff0000u);
    v[4 * i + 2] = __uint_as_float(u[i].y << 16); v[4 * i + 3] = __uint_as_float(u[i].y & 0xffff0000u);
  }
  float s = 0.f;
#pragma unroll
  for (int i = 0; i < 20; i++) s += v[i];
#pragma unroll
  for (int o = 16; o; o >>= 1) s += __shfl_xor_sync(~0u, s, o);
  const float mean = s * (1.0f / DM);
  float q = 0.f;
#pragma unroll
  for (int i = 0; i < 20; i++) { float d = v[i] - mean; q += d * d; }
#pragma unroll
  for (int o = 16; o; o >>= 1) q += __shfl_xor_sync(~0u, q, o);
  const float mb = bfr(mean), rs = 1.0f / bfr(sqrtf(bfr(bfr(q * (1.0f / DM)) + 1e-5f)));
  uint2* dst = reinterpret_cast<uint2*>(g_xn + (size_t)row * DM);
#pragma unroll
  for (int i = 0; i < 5; i++) {
    uint2 o;
    o.x = pack2(bfr(v[4 * i + 0] - mb) * rs, bfr(v[4 * i + 1] - mb) * rs);
    o.y = pack2(bfr(v[4 * i + 2] - mb) * rs, bfr(v[4 * i + 3] - mb) * rs);
    dst[i * 32 + lane] = o;
  }
}
__device__ __forceinline__ void wait_flag(const unsigned* f, unsigned target) {
  unsigned v; int n = 0;
  while (true) {
    asm volatile("ld.acquire.gpu.global.u32 %0, [%1];" : "=r"(v) : "l"(f) : "memory");
    if (v >= target) break;
    if (++n > (1 << 21)) __trap();
    __nanosleep(100);
  }
  asm volatile("fence.proxy.async.global;" ::: "memory");
}

namespace ck {
constexpr int CL = 6, NCL = 16, NRF = 8, NSS = 40 - NRF, NTP = 1;
constexpr uint32_t OFF_H = 0, OFF_WV = 51200, OFF_WO = OFF_WV + NSS * 2048, OFF_Q = OFF_WO + 86016, OFF_K = OFF_Q + 5120,
                   OFF_OG = OFF_K + 5120, OFF_RA = OFF_OG + 6144, OFF_P = OFF_RA + 3840, OFF_RT = OFF_P + 3200,
                   OFF_BAR = OFF_RT + 5120, SMEM = OFF_BAR + 256;
constexpr uint32_t B_X = 0, B_A = 8, B_T = 16, B_W = 24, B_WR = 32, B_B = 40  , B_XF = 88, B_DUMMY = 96, B_WO = 104,
                   B_ST = 128  ;
enum { NB_M = 1, NB_QK = 2, NB_PM = 3, NB_V = 4, NB_TS = 5, NB_P = 6, NB_G = 7, NB_R = 8  , NB_S = 12, NB_V2 = 13, NB_G1 = 14 };
static_assert(SMEM <= 232448, "smem");
static_assert(OFF_WO % 1024 == 0 && OFF_Q % 1024 == 0, "align");
}
__device__ __forceinline__ uint32_t opq(uint32_t x) { asm volatile("" : "+r"(x)); return x; }

__device__ __forceinline__ uint32_t memrow_addr(uint32_t sb, uint32_t col0, uint32_t m) {
  return sb + ck::OFF_H + (col0 >> 6) * 5120 + 4096 + m * 128 + ((((col0 >> 3) & 7) ^ m) << 4);
}
constexpr int VLEAD = 5;
constexpr int LW = 24, LW2 = 33;
constexpr int DEPTH = 2;
template <int N> struct MemLoad { float4 c[N]; };
template <int N>
__device__ __forceinline__ void memload_issue(MemLoad<N>& m, int s, uint32_t warp, uint32_t lane) {
  const float4* p = g_acc + (s * ACC_CHUNKS + warp * 160) + lane;
#pragma unroll
  for (int q = 0; q < N; q++) m.c[q] = ld_relaxed4(p + q * 32);
}
template <int N>
__device__ __forceinline__ void memload_finish(MemLoad<N>& m, int s, uint32_t warp, uint32_t lane0, uint32_t sb, float full) {
  const uint32_t lane = opq(lane0);
  const uint32_t a4 = memrow_addr(sb, warp * 48 + (lane >> 3) * 8, lane & 7), a2 = memrow_addr(sb, warp * 48 + 32 + ((lane >> 3) & 1) * 8, lane & 7);
  const uint32_t a1 = memrow_addr(sb, 576 + warp * 8, lane & 7);
  int n = 0;
  while (true) {
    bool ok = true;
#pragma unroll
    for (int q = 0; q < N; q++) ok = ok && m.c[q].w == full;
    if (__all_sync(~0u, ok)) break;
    if (++n > SPIN_LIMIT) __trap();
    memload_issue(m, s, warp, opq(lane0));
  }
  const float4* c = m.c;
  stsm4t(a4, pack2(c[0].x, c[1].x), pack2(c[2].x, c[3].x), pack2(c[0].y, c[1].y), pack2(c[2].y, c[3].y));
  stsm2t(a2, pack2(c[0].z, c[1].z), pack2(c[2].z, c[3].z));
  if (N == 5) stsm1t(a1, pack2(c[N - 1].x, c[N - 1].y + c[N - 1].z));
}
#define WO_PREFETCH() _Pragma("unroll") for (int i = 0; i < 6; i++) \
  ldsm4t(f[i / 3][4 * (i % 3)], f[i / 3][4 * (i % 3) + 1], f[i / 3][4 * (i % 3) + 2], f[i / 3][4 * (i % 3) + 3], wo + (i % 3) * 12288 + (i / 3) * 2048)
#define HOFF(k) ((uint64_t)((((k) >> 2) * 5120 + ((k) & 3) * 32) >> 4))

template <bool LOADS>
__device__ __forceinline__ void token_qk(const uint32_t* a, int s, uint32_t sb, uint32_t warp, uint32_t lane0, uint32_t zero, bool lead) {
  using namespace ck;
  const uint32_t bar = sb + OFF_BAR;
  float d[16];
  MemLoad<5> ml;
  mbar_wait(bar + B_X, (s + 1) & 1);
  const uint32_t db = opq((uint32_t)mkdesc(sb + OFF_H, 16, 1024, 1));
  WG_FENCE();
  wg_rs32x<0>(d, a[0], a[1], a[2], a[3], db);
#pragma unroll
  for (int k = 1; k < 40; k++) {
    wg_rs32x<1>(d, a[4 * k], a[4 * k + 1], a[4 * k + 2], a[4 * k + 3], db + (uint32_t)HOFF(k));
    if (LOADS && (k == LW || k == LW2)) WG_COMMIT();
  }
  WG_COMMIT();
  if (LOADS) { WG_WAIT(2); if (lead) WG_WAIT(1); do { memload_issue(ml, s, warp, opq(lane0)); } while (zero >> 31); }
  WG_WAIT(0);
  const uint32_t e0 = pack2(d[0], d[1]);
  const uint32_t lane = opq(lane0), wg = warp >> 2, w4 = warp & 3;
  const uint32_t mat = lane >> 3, i = lane & 7, h = mat & 1, j0 = mat >> 1;
  const uint32_t ep0 = sb + OFF_Q + wg * 5120 + (8 * j0 + i) * 128 + (((2 * w4 + h) ^ i) << 4), ep1 = ep0 + 2048;
  stsm4t(ep0, e0, pack2(d[2], d[3]), pack2(d[4], d[5]), pack2(d[6], d[7]));
  stsm4t(ep1, pack2(d[8], d[9]), pack2(d[10], d[11]), pack2(d[12], d[13]), pack2(d[14], d[15]));
  if (LOADS) memload_finish(ml, s, warp, lane, sb, __uint_as_float(__float_as_uint((float)NCL) + (e0 & zero)));
}

__global__ void __launch_bounds__(384, 1)
chain_kernel(const __grid_constant__ CUtensorMap tm_x, const __grid_constant__ CUtensorMap tm_wv, const __grid_constant__ CUtensorMap tm_wo,
             const __grid_constant__ CUtensorMap tm_wq, const __grid_constant__ CUtensorMap tm_wk, const bf16* __restrict__ mem0,
             const bf16* __restrict__ x, uint32_t zero) {
  using namespace ck;
  extern __shared__ __align__(1024) unsigned char smem[];
  const uint32_t sb = smem_u32(smem);
  const uint32_t tid0 = threadIdx.x;
  const uint32_t warp = __shfl_sync(~0u, threadIdx.x >> 5, 0);
  const int rank = blockIdx.x % CL, cluster = blockIdx.x / CL;
  const int hb = (rank / 3) * 3, j3 = rank % 3;
  const uint32_t bar = sb + OFF_BAR;
  if (sb & 1023) __trap();

  asm volatile("griddepcontrol.launch_dependents;");
  const int gw = (tid0 >> 5) * 96 + blockIdx.x;
  uint2 xu[2][5];
  uint4 m0u[5];
#pragma unroll
  for (int r = 0; r < 5; r++) m0u[r] = __ldg(reinterpret_cast<const uint4*>(mem0) + (tid0 & 127) + r * 128);
#pragma unroll
  for (int r = 0; r < 2; r++) {
    const int row = min(gw + r * 1152, SEQ - 1);
#pragma unroll
    for (int j = 0; j < 5; j++) xu[r][j] = __ldg(reinterpret_cast<const uint2*>(x + (size_t)row * DM) + j * 32 + (tid0 & 31));
  }
  if (tid0 == 0) {
    mbar_init(bar + B_X, 1); mbar_init(bar + B_A, 1); mbar_init(bar + B_T, 1); mbar_init(bar + B_W, 1); mbar_init(bar + B_WR, 1);
    for (int i = 0; i < 3; i++) mbar_init(bar + B_B + 8 * i, 1);
    for (int i = 0; i < 10; i++) mbar_init(bar + B_ST + 8 * i, 1);
    mbar_init(bar + B_XF, 1); mbar_init(bar + B_WO, 1);
    asm volatile("fence.mbarrier_init.release.cluster;" ::: "memory");
    mbar_expect(bar + B_A, 3 * 1024); mbar_expect(bar + B_T, 2 * 2560);
    for (int i = 0; i < 3; i++) mbar_expect(bar + B_B + 8 * i, 2048);
    for (int i = 0; i < 10; i++) mbar_expect(bar + B_ST + 8 * i, 16384);
    mbar_expect(bar + B_XF, CL * 4);
    mbar_expect(bar + B_X, 40960);
    mbar_expect(bar + B_WR, NRF * 2048);
    mbar_expect(bar + B_W, NSS * 2048); mbar_expect(bar + B_WO, (rank < 4 ? 7 : 6) * 12288);
    tma2d(sb + OFF_H, &tm_wv, blockIdx.x * 64, NSS * 16, bar + B_WR);
  }
  {
    const float4 z = make_float4(0.f, 0.f, 0.f, 0.f);
    for (int j = blockIdx.x * 384 + tid0; j < NSEG * ACC_CHUNKS; j += 96 * 384) g_acc[j] = z;
    for (int j = blockIdx.x * 384 + tid0; j < 20 * 4096; j += 96 * 384) g_part[j] = z;
  }
#pragma unroll 1
  for (int r = 0; r < 2; r++) {
    if (gw + r * 1152 < SEQ) ln_row(xu[0], gw + r * 1152, tid0 & 31);
#pragma unroll
    for (int j = 0; j < 5; j++) xu[0][j] = xu[1][j];
    if (r == 0 && tid0 < 2 * DEPTH) {
      const uint32_t wg = tid0 & 1, i = tid0 >> 1;
      tma2d(sb + (wg == 0 ? OFF_WO + i * 16384 : i < 4 ? OFF_WV + i * 16384 : OFF_Q), wg == 0 ? &tm_wq : &tm_wk, blockIdx.x * 64, i * 128,
            bar + B_ST + 8 * (wg * 5 + i));
    }
    __syncwarp();
  }
  __threadfence();
  __syncthreads();
  if (tid0 == 320) atomicAdd(&g_flag[F_LN], 1u);

  if (warp < 8) {
    asm volatile("setmaxnreg.inc.sync.aligned.u32 208;");
    const uint32_t lane0 = __shfl_sync(~0u, opq(threadIdx.x & 31), threadIdx.x & 31);
    uint32_t a[160];
    {
      const uint32_t wg = warp >> 2, l7 = lane0 & 7, l3 = lane0 >> 3, t128 = tid0 & 127;
      const uint32_t lo = ((l3 >> 1) * 8 + l7) * 128 + (((2 * (warp & 3) + (l3 & 1)) ^ l7) << 4);
#pragma unroll
      for (int i = 0; i < 5; i++) {
        const uint32_t base = sb + (wg == 0 ? OFF_WO + i * 16384 : i < 4 ? OFF_WV + i * 16384 : OFF_Q) + lo;
        mbar_wait(bar + B_ST + 8 * (wg * 5 + i), 0);
        if (i + DEPTH < 5 && t128 == 0)
          tma2d(sb + (wg == 0 ? OFF_WO + (i + DEPTH) * 16384 : i + DEPTH < 4 ? OFF_WV + (i + DEPTH) * 16384 : OFF_Q), wg == 0 ? &tm_wq : &tm_wk,
                blockIdx.x * 64, (i + DEPTH) * 128, bar + B_ST + 8 * (wg * 5 + i + DEPTH));
        __syncwarp();
#pragma unroll
        for (int k = 0; k < 8; k++) ldsm4t(a[32 * i + 4 * k], a[32 * i + 4 * k + 1], a[32 * i + 4 * k + 2], a[32 * i + 4 * k + 3], base + k * 2048);
        asm volatile("" :: "r"(a[32 * i]), "r"(a[32 * i + 4]), "r"(a[32 * i + 8]), "r"(a[32 * i + 12]), "r"(a[32 * i + 16]), "r"(a[32 * i + 20]), "r"(a[32 * i + 24]), "r"(a[32 * i + 28]) : "memory");
        bar_sync(NB_R + wg, 128);
        if (wg == 1) {
          if (i >= 3 && t128 < 2) tma2d(sb + OFF_WV + ((i - 3) * 2 + t128) * 16384, &tm_wv, blockIdx.x * 64, ((i - 3) * 2 + t128) * 128, bar + B_W);
        } else if (i == 4) {
          const int t = t128 / 6, d = t128 % 6;
          if (t < (rank < 4 ? 7 : 6)) tma2d(sb + OFF_WO + t * 12288 + d * 2048, &tm_wo, t < 6 ? rank * 96 + t * 16 : 576 + rank * 16,
                                            cluster * 384 + ((rank + CL - d) % CL) * 64, bar + B_WO);
        }
        __syncwarp();
      }
      bar_sync(NB_QK, 256);
      asm volatile("barrier.cluster.arrive.relaxed.aligned;" ::: "memory");
    }
    token_qk<false>(a, -1, sb, warp, lane0, zero, false);
    asm volatile("barrier.cluster.wait.acquire.aligned;" ::: "memory");
    const float sc = 0.07216878364870322f * 1.4426950408889634f;

    for (int s = 0;; s++) {
      uint32_t lane;
      {
        const uint32_t ln = opq(lane0);
        const uint32_t x0 = sb + OFF_H + 4096 + (ln & 7) * 128 + (((ln >> 3) ^ (ln & 7)) << 4), x1 = x0 ^ 64;
        float c[16];
#pragma unroll
        for (int i = 0; i < 16; i++) c[i] = 0.f;
        uint32_t bf[1][16];
        bar_sync(NB_M, 384);
#pragma unroll
        for (int k = 0; k < 40; k += 2) {
          uint32_t* b = bf[0] + 12;
          ldsm4(b[0], b[1], b[2], b[3], ((k & 2) ? x1 : x0) + (k >> 2) * 5120);
          float* d = c + ((k & 2) ? 8 : 0);
          mma16816(d, a[4 * k], a[4 * k + 1], a[4 * k + 2], a[4 * k + 3], b[0], b[1]);
          mma16816(d + 4, a[4 * k + 4], a[4 * k + 5], a[4 * k + 6], a[4 * k + 7], b[2], b[3]);
        }
#pragma unroll
        for (int i = 0; i < 4; i++) c[i] = (c[i] + c[4 + i]) + (c[8 + i] + c[12 + i]);
        asm volatile("add.u32 %0, %1, %2;" : "=r"(lane) : "r"(lane0), "r"(bf[0][15] & zero));
        const uint32_t qst = sb + OFF_Q + (warp >> 2) * 5120 + (32 + (lane & 7)) * 128 + (((2 * (warp & 3) + ((lane >> 3) & 1)) ^ (lane & 7)) << 4);
        stsm2t(qst, pack2(c[0], c[1]), pack2(c[2], c[3]));
      }
      const uint32_t l7 = lane & 7, l3 = lane >> 3;
      fence_async();
      bar_arrive(NB_S, 384);
      if (s == NSEG - 1) break;
      if (s == 0) { mbar_wait(bar + B_WO, 0); if (tid0 == 64) atomicAdd(&g_flag[F_W], 1u); }
      const uint32_t grp = warp >> 2, kq = warp & 3;
      const uint32_t wo = sb + OFF_WO + grp * 36864 + kq * 512 + ((l3 >> 1) * 8 + l7) * 32 + (((l3 & 1) ^ (kq >> 1) ^ (l7 >> 2)) << 4);
      uint32_t f[2][12];
      if (warp >= 5) {
        const uint32_t g = warp - 5;
        const uint32_t r4 = sb + OFF_RA + g * 256 + (l3 >> 1) * 1024 + (lane & 15) * 16, r2 = sb + OFF_RA + g * 256 + 2048 + (lane & 15) * 16;
        mbar_wait(bar + B_A, s & 1);
        uint32_t t0, t1, t2, t3, t4, t5;
        ldsm4t(t0, t1, t2, t3, r4);
        asm volatile("ldmatrix.sync.aligned.m8n8.x2.trans.shared.b16 {%0,%1}, [%2];" : "=r"(t4), "=r"(t5) : "r"(r2) : "memory");
        float p0 = (__uint_as_float(t0 << 16) + __uint_as_float(t2 << 16)) + __uint_as_float(t4 << 16);
        float p1 = (__uint_as_float(t0 & 0xffff0000u) + __uint_as_float(t2 & 0xffff0000u)) + __uint_as_float(t4 & 0xffff0000u);
        float p2 = (__uint_as_float(t1 << 16) + __uint_as_float(t3 << 16)) + __uint_as_float(t5 << 16);
        float p3 = (__uint_as_float(t1 & 0xffff0000u) + __uint_as_float(t3 & 0xffff0000u)) + __uint_as_float(t5 & 0xffff0000u);
        if (g == 2) { p2 = -INFINITY; p3 = -INFINITY; }
        float mx = fmaxf(fmaxf(p0, p1), fmaxf(p2, p3));
        mx = fmaxf(mx, __shfl_xor_sync(~0u, mx, 1)); mx = fmaxf(mx, __shfl_xor_sync(~0u, mx, 2));
        mx *= sc;
        const uint32_t e0 = pack2(ex2(fmaf(p0, sc, -mx)), ex2(fmaf(p1, sc, -mx))), e1 = pack2(ex2(fmaf(p2, sc, -mx)), ex2(fmaf(p3, sc, -mx)));
        const uint32_t pw = sb + OFF_P + lane * 16;
        sts1u(pw + (g == 2 ? 512 : g * 4), e0);
        sts1u(pw + (g == 2 ? 1024 : 8 + g * 4), e1);
        sts1f(pw + 516 + g * 4, mx);
        bar_arrive(NB_PM, 224);
      }
      if (warp == 1 || warp == 2) {
        const uint32_t rb = mapa(sb, lane < CL ? lane : 0);
        bar_sync(NB_V2, 192);
        if (warp == 1 && lane < CL) st_async1(rb + OFF_BAR + B_DUMMY, 0u, rb + OFF_BAR + B_XF);
        if (warp == 2) {
          if (lane == 0) mbar_expect(bar + B_X, 40960);
          mbar_wait(bar + B_XF, s & 1);
          if (lane == 0) mbar_expect(bar + B_XF, CL * 4);
          const int c2 = rank + 6 * lane;
          if (c2 < 10) tma2d_mc(sb + OFF_H + c2 * 5120, &tm_x, c2 * 64, (s + 1) * 32, bar + B_X, (uint16_t)0x3f);
          __syncwarp();
        }
      }
      {
        const uint32_t og = sb + OFF_OG + kq * 256 + (lane ^ ((kq & 1) << 2)) * 8;
        float v[12];
#pragma unroll
        for (int i = 0; i < 12; i++) v[i] = 0.f;
        bar_sync(NB_V, 384);
        WO_PREFETCH();
        bar_sync(NB_TS, 384);
        const bool lead = grp == (uint32_t)(cluster & 1);
        if (!lead) bar_sync(NB_QK, 256);
#pragma unroll
        for (int u = 0; u < 3; u++) {
          if (u == 1 && lead) bar_arrive(NB_QK, 256);
          mbar_wait(bar + B_B + 8 * u, s & 1);
          const float2 o0 = lds2f(og + u * 2048), o1 = lds2f(og + u * 2048 + 1024);
#pragma unroll
          for (int h = 0; h < 2; h++) {
            uint32_t* ff = f[h];
#pragma unroll
            for (int i = 0; i < 3; i++)
              mma16816(v + 4 * i, ff[4 * i], ff[4 * i + 1], ff[4 * i + 2], ff[4 * i + 3], __float_as_uint(h ? o1.x : o0.x), __float_as_uint(h ? o1.y : o0.y));
            if (u < 2) {
#pragma unroll
              for (int i = 0; i < 3; i++) ldsm4t(ff[4 * i], ff[4 * i + 1], ff[4 * i + 2], ff[4 * i + 3], wo + (2 * u + 2 + h) * 2048 + i * 12288);
            }
          }
        }
        const uint32_t xb = sb + OFF_Q + grp * 4608;
#pragma unroll
        for (int i = 1; i < 4; i++) {
          const uint32_t x = xb + ((i ^ kq) * 3 + (i - 1)) * 384;
          sts2f(x + lane * 8, v[i], v[4 + i]); sts1f(x + 256 + lane * 4, v[8 + i]);
        }
        if (!lead) bar_arrive(NB_G1, 384);
        float4* o = g_acc + (s * ACC_CHUNKS + (2 * rank + grp) * 160 + kq * 32) + lane;
        const uint32_t y = xb + kq * 1152;
        bar_sync(NB_R + grp, 128);
        const float2 p0 = lds2f(y + lane * 8), p1 = lds2f(y + 384 + lane * 8), p2 = lds2f(y + 768 + lane * 8);
        const float q0 = lds1f(y + 256 + lane * 4), q1 = lds1f(y + 640 + lane * 4), q2 = lds1f(y + 1024 + lane * 4);
        red4(o, (v[0] + p0.x) + (p1.x + p2.x), (v[4] + p0.y) + (p1.y + p2.y), (v[8] + q0) + (q1 + q2), 1.0f);
      }
      if (grp == (uint32_t)(cluster & 1)) { bar_arrive(NB_G, 384); bar_sync(NB_G1, 384); }
      else bar_sync(NB_G, 384);
      token_qk<true>(a, s, sb, warp, lane0, zero, grp == (uint32_t)(cluster & 1));
    }
    cluster_sync();
  } else {
    asm volatile("setmaxnreg.dec.sync.aligned.u32 88;");
    const uint32_t lane0 = __shfl_xor_sync(~0u, opq((threadIdx.x & 31) ^ 1), 1);
    asm volatile("barrier.cluster.arrive.relaxed.aligned;" ::: "memory");
    uint32_t wv[4 * NRF];
    {
      const int i = tid0 - 256;
      mbar_wait(bar + B_WR, 0);
      const uint32_t l7 = lane0 & 7, l3 = lane0 >> 3;
#pragma unroll
      for (int k = 0; k < NRF; k++)
        ldsm4t(wv[4 * k], wv[4 * k + 1], wv[4 * k + 2], wv[4 * k + 3], sb + OFF_H + k * 2048 + ((l3 >> 1) * 8 + l7) * 128 + (((2 * (warp - 8) + (l3 & 1)) ^ l7) << 4));
      asm volatile("" :: "r"(wv[0]), "r"(wv[4]), "r"(wv[8]), "r"(wv[12]), "r"(wv[16]), "r"(wv[20]), "r"(wv[24]), "r"(wv[28]) : "memory");
      bar_sync(NB_P, 128);
#pragma unroll
      for (int r = 0; r < 5; r++) { const uint32_t j = i + r * 128; sts4u(memrow_addr(sb, (j % 80) * 8, j / 80), m0u[r]); }
      fence_async();
      if (i == 96) {
        wait_flag(&g_flag[F_LN], 96);
        for (int c = 0; c < 10; c++) tma2d(sb + OFF_H + c * 5120, &tm_x, c * 64, 0, bar + B_X);
      }
      __syncwarp();
    }
    mbar_wait(bar + B_W, 0);
    asm volatile("barrier.cluster.wait.acquire.aligned;" ::: "memory");
    const float sc = 0.07216878364870322f * 1.4426950408889634f;

    bar_arrive(NB_M, 384);
    for (int s = 0; s < NSEG; s++) {
      const bool last = s == NSEG - 1;
      uint32_t va[10];
      {
        uint32_t wt_[4 * NTP];
        {
          const uint32_t ln = opq(lane0), l7 = ln & 7, l3 = ln >> 3;
#pragma unroll
          for (int k = 0; k < NTP; k++)
            ldsm4t(wt_[4 * k], wt_[4 * k + 1], wt_[4 * k + 2], wt_[4 * k + 3],
                   sb + OFF_WV + (NSS - NTP + k) * 2048 + ((l3 >> 1) * 8 + l7) * 128 + (((2 * (warp - 8) + (l3 & 1)) ^ l7) << 4));
        }
        mbar_wait(bar + B_X, s & 1);
        float v[20];
        uint64_t db = mkdesc(sb + OFF_H, 16, 1024, 1), da = mkdesc(sb + OFF_WV, 1024, 1024, 1);
        OPAQUE64(db); OPAQUE64(da);
        uint64_t dk = mkdesc(sb + OFF_K, 16, 1024, 1), dq = mkdesc(sb + OFF_Q + 4096, 16, 1024, 1);
        OPAQUE64(dk); OPAQUE64(dq);
        const uint32_t ra = OFF_RA + j3 * 1024 + (warp - 8) * 256 + opq(lane0) * 4;
        float sm[4];
        bar_sync(NB_S, 384);
        WG_FENCE();
        wg_ss8<0>(sm, dk, dq); wg_ss8<1>(sm, dk + 2, dq + 2); wg_ss8<1>(sm, dk + 4, dq + 4); wg_ss8<1>(sm, dk + 6, dq + 6);
        WG_COMMIT();
        wg_ss40<0, 1>(v, da, db);
#pragma unroll
        for (int k = 1; k < VLEAD; k++) wg_ss40<1, 1>(v, da + (uint64_t)(k * 128), db + HOFF(k));
        WG_COMMIT();
        WG_WAIT(1);
        {
          const uint32_t x = pack2(sm[0], sm[1]), y = pack2(sm[2], sm[3]);
#pragma unroll
          for (int d = 0; d < 3; d++) {
            const uint32_t rb = mapa(sb, hb + (j3 + 1 + d) % 3);
            st_async1(rb + ra, x, rb + OFF_BAR + B_A); st_async1(rb + ra + 128, y, rb + OFF_BAR + B_A);
          }
        }
#pragma unroll
        for (int k = VLEAD; k < NSS - NTP; k++) wg_ss40<1, 1>(v, da + (uint64_t)(k * 128), db + HOFF(k));
#pragma unroll
        for (int k = 0; k < NTP; k++) wg_rs40<1>(v, wt_[4 * k], wt_[4 * k + 1], wt_[4 * k + 2], wt_[4 * k + 3], db + HOFF(NSS - NTP + k));
#pragma unroll
        for (int k = NSS; k < 40; k++) wg_rs40<1>(v, wv[4 * (k - NSS)], wv[4 * (k - NSS) + 1], wv[4 * (k - NSS) + 2], wv[4 * (k - NSS) + 3], db + HOFF(k));
        WG_COMMIT();
        WG_WAIT(0);
#pragma unroll
        for (int i = 0; i < 10; i++) va[i] = pack2(v[2 * i], v[2 * i + 1]);
      }
      const uint32_t lane = opq(lane0), w4 = warp - 8, wt = w4 * 32 + lane;
      if (!last) {
        bar_arrive(NB_V2, 192);
        bar_sync(NB_PM, 224);
        const uint4 pa = lds4u(sb + OFF_P + lane * 16), pc = lds4u(sb + OFF_P + 512 + lane * 16);
        float o[6][4], os[4], ot[4];
#pragma unroll
        for (int i = 0; i < 4; i++) { o[0][i] = o[1][i] = o[2][i] = o[3][i] = o[4][i] = o[5][i] = os[i] = ot[i] = 0.f; }
        mma16816(os, pa.x, pa.y, pa.z, pa.w, 0x3f803f80u, 0x3f803f80u);
        mma1688(ot, pc.x, pc.y, 0x3f803f80u);
        mma16816(o[0], pa.x, pa.y, pa.z, pa.w, va[0], va[2]);
        mma16816(o[1], pa.x, pa.y, pa.z, pa.w, va[1], va[3]);
        mma16816(o[2], pa.x, pa.y, pa.z, pa.w, va[4], va[6]);
        mma16816(o[3], pa.x, pa.y, pa.z, pa.w, va[5], va[7]);
        mma1688(o[4], pc.x, pc.y, va[8]);
        mma1688(o[5], pc.x, pc.y, va[9]);
        o[2][0] = o[2][2]; o[2][1] = o[2][3]; o[3][0] = o[3][2]; o[3][1] = o[3][3];
        const float ma = __uint_as_float(pc.y), mb = __uint_as_float(pc.z), mc = __uint_as_float(pc.w), mx = fmaxf(fmaxf(ma, mb), mc);
        float fa = ex2(ma - mx), fb = ex2(mb - mx), fc = ex2(mc - mx);
        const float inv = rcp(fmaf(fa, os[0], fmaf(fb, os[2], fc * ot[0])));
        fa *= inv; fb *= inv; fc *= inv;
        const uint32_t x = pack2(fmaf(fa, o[0][0], fmaf(fb, o[2][0], fc * o[4][0])), fmaf(fa, o[0][1], fmaf(fb, o[2][1], fc * o[4][1])));
        const uint32_t y = pack2(fmaf(fa, o[1][0], fmaf(fb, o[3][0], fc * o[5][0])), fmaf(fa, o[1][1], fmaf(fb, o[3][1], fc * o[5][1])));
#pragma unroll
        for (int d = 0; d < CL; d++) {
          int r = rank + d; if (r >= CL) r -= CL;
          const uint32_t rb = mapa(sb, r);
          st_async2(rb + OFF_OG + wt * 8 + d * 1024, x, y, rb + OFF_BAR + B_B + 8 * (d >> 1));
        }
        bar_arrive(NB_V, 384);
        if (wt == 0) mbar_expect(bar + B_A, 3 * 1024);
      }
      uint32_t e[5];
      {
        float v[20];
        uint64_t da = mkdesc(sb + OFF_Q, 16, 512, 1), db = mkdesc(sb + OFF_K, 16, 1024, 1);
        OPAQUE64(db); OPAQUE64(da);
        WG_FENCE();
        wg_ss40<0, 0>(v, da, db);
        wg_ss40<1, 0>(v, da + 2, db + 2);
        wg_ss40<1, 0>(v, da + 4, db + 4);
        wg_ss40<1, 0>(v, da + 6, db + 6);
        WG_COMMIT();
        WG_WAIT(0);
#pragma unroll
        for (int i = 0; i < 5; i++) e[i] = pack2(v[4 * i], v[4 * i + 1]);
      }
      if (!last) {
        bar_arrive(NB_TS, 384);
        if (!((w4 == 1 || w4 == 2) && rank < 4)) bar_arrive(NB_G1, 384);
        if (w4 == 3) {
          if ((s & 3) == 0 && s > 0 && lane == 0) { __threadfence(); atomicAdd(&g_flag[(s >> 2) - 1], 1u); }
          __syncwarp();
        } else if (w4 == 0) {
          const uint32_t ln = blockIdx.x * 32 + lane;
          if (s + 3 < NSEG) {
            if (ln < 240) asm volatile("prefetch.global.L2 [%0];" :: "l"(g_acc + (s + 3) * ACC_CHUNKS + ln * 8));
            else if (ln >= 256 && ln < 576) asm volatile("prefetch.global.L2 [%0];" :: "l"(g_xn + (s + 3) * 32 * DM + (ln - 256) * 64));
          }
        } else if (rank < 4) {
          if (s == 0) mbar_wait(bar + B_WO, 0);
          const uint32_t kh = w4 - 1, l7 = lane & 7, l3 = lane >> 3;
          const uint32_t wo = sb + OFF_WO + 6 * 12288 + kh * 2048 + ((l3 >> 1) * 8 + l7) * 32 + (((l3 & 1) ^ (l7 >> 2)) << 4);
          const uint32_t og = sb + OFF_OG + kh * 1024 + lane * 8;
          float u[4] = {0.f, 0.f, 0.f, 0.f};
#pragma unroll
          for (int it = 0; it < 3; it++) {
            uint32_t ff[16];
#pragma unroll
            for (int kk = 0; kk < 4; kk++) ldsm4t(ff[4 * kk], ff[4 * kk + 1], ff[4 * kk + 2], ff[4 * kk + 3], wo + it * 4096 + kk * 512);
            mbar_wait(bar + B_B + 8 * it, s & 1);
#pragma unroll
            for (int kk = 0; kk < 4; kk++) {
              const float2 o = lds2f(og + it * 2048 + kk * 256);
              mma16816(u, ff[4 * kk], ff[4 * kk + 1], ff[4 * kk + 2], ff[4 * kk + 3], __float_as_uint(o.x), __float_as_uint(o.y));
            }
          }
          const uint32_t xb = sb + OFF_RA + lane * 8;
          sts2f(xb + kh * 256, kh ? u[0] : u[2], kh ? u[1] : u[3]);
          bar_arrive(NB_G1, 384);
          float4* o = g_acc + (s * ACC_CHUNKS + (2 * rank + kh) * 160 + 128) + lane;
          bar_sync(NB_R + 2, 64);
          const float2 x = lds2f(xb + 256 - kh * 256);
          red4(o, (kh ? u[2] : u[0]) + x.x, (kh ? u[3] : u[1]) + x.y, 0.f, 1.0f);
        }
        bar_sync(NB_G, 384);
        if (wt < 3) mbar_expect(bar + B_B + 8 * wt, 2048);
      } else {
        mbar_wait(bar + B_A, s & 1);
      }
      {
#pragma unroll
        for (int d = 1; d <= 2; d++) {
          const uint32_t rb = mapa(sb, hb + (j3 + d) % 3);
          st_async4(rb + OFF_RT + (2 - d) * 2560 + wt * 16, e[0], e[1], e[2], e[3], rb + OFF_BAR + B_T);
          st_async1(rb + OFF_RT + (2 - d) * 2560 + 2048 + wt * 4, e[4], rb + OFF_BAR + B_T);
        }
      }
      mbar_wait(bar + B_T, s & 1);
      float p[10];
#pragma unroll
      for (int i = 0; i < 5; i++) { p[2 * i] = __uint_as_float(e[i] << 16); p[2 * i + 1] = __uint_as_float(e[i] & 0xffff0000u); }
#pragma unroll
      for (int d = 0; d < 2; d++) {
        const uint4 x = lds4u(sb + OFF_RT + d * 2560 + wt * 16);
        const uint32_t y = __float_as_uint(lds1f(sb + OFF_RT + d * 2560 + 2048 + wt * 4));
        p[0] += __uint_as_float(x.x << 16); p[1] += __uint_as_float(x.x & 0xffff0000u);
        p[2] += __uint_as_float(x.y << 16); p[3] += __uint_as_float(x.y & 0xffff0000u);
        p[4] += __uint_as_float(x.z << 16); p[5] += __uint_as_float(x.z & 0xffff0000u);
        p[6] += __uint_as_float(x.w << 16); p[7] += __uint_as_float(x.w & 0xffff0000u);
        p[8] += __uint_as_float(y << 16); p[9] += __uint_as_float(y & 0xffff0000u);
      }
      if (wt == 0) mbar_expect(bar + B_T, 2 * 2560);
      MemLoad<4> ml;
#pragma unroll
      for (int q = 0; q < 4; q++) ml.c[q] = make_float4(0.f, 0.f, 0.f, 0.f);
      if (!last) memload_issue(ml, s, warp, lane);
      {
        const int tq = 8 * w4 + (lane >> 2) - 2 * (lane & 3);
        float mx = fmaxf(p[8], p[9]);
#pragma unroll
        for (int i = 0; i < 8; i++) { if (8 * (i >> 1) + (i & 1) > tq) p[i] = -INFINITY; mx = fmaxf(mx, p[i]); }
        mx = fmaxf(mx, __shfl_xor_sync(~0u, mx, 1)); mx = fmaxf(mx, __shfl_xor_sync(~0u, mx, 2));
        float sum = 0.f;
#pragma unroll
        for (int i = 0; i < 10; i++) { p[i] = ex2(fmaf(p[i], sc, -mx * sc)); sum += p[i]; }
        sum += __shfl_xor_sync(~0u, sum, 1); sum += __shfl_xor_sync(~0u, sum, 2);
        const float inv = rcp(sum);
        const uint32_t pr = sb + OFF_P + (lane >> 3) * 800 + w4 * 32 + (lane & 7) * 4;
#pragma unroll
        for (int i = 0; i < 5; i++) sts1u(pr + i * 128, pack2(p[2 * i] * inv, p[2 * i + 1] * inv));
        sts1u(pr + 640, 0u);
      }
      if (!last) {
        memload_finish(ml, s, warp, lane, sb, (float)NCL);
        bar_arrive(NB_M, 384);
      }
      fence_async();
      bar_sync(NB_P, 128);
      {
        float o[16];
        uint64_t db = mkdesc(sb + OFF_P, 128, 800, 0);
        OPAQUE64(db);
        uint32_t vb[10];
#pragma unroll
        for (int i = 0; i < 10; i++) asm volatile("add.u32 %0, %1, %2;" : "=r"(vb[i]) : "r"(va[i]), "r"(zero));
        WG_FENCE();
        wg_rs32<0>(o, vb[0], vb[1], vb[2], vb[3], db);
        wg_rs32<1>(o, vb[4], vb[5], vb[6], vb[7], db + 16);
        wg_rs32<1>(o, vb[8], vb[9], 0u, 0u, db + 32);
        WG_COMMIT();
        uint4* dst = reinterpret_cast<uint4*>(g_oT) + ((s * HD + blockIdx.x * 64 + w4 * 16) * 4 + lane);
        WG_WAIT(0);
        dst[0] = make_uint4(pack2(o[0], o[1]), pack2(o[4], o[5]), pack2(o[8], o[9]), pack2(o[12], o[13]));
        dst[32] = make_uint4(pack2(o[2], o[3]), pack2(o[6], o[7]), pack2(o[10], o[11]), pack2(o[14], o[15]));
      }
    }
    bar_sync(NB_P, 128);
    if (tid0 == 256) { __threadfence(); atomicAdd(&g_flag[15], 1u); }
    cluster_sync();
  }
}

namespace hk {
constexpr int STAGES = 4, STAGE = 49152, OFF_ST = STAGES * STAGE, OFF_BAR = OFF_ST + 32768, SMEM = OFF_BAR + 1024, NCTA = NHELP;
constexpr int N_G1 = 192, SB0 = 12  , N_FULL = 5 * SB0, N_ITEMS = N_G1 + 20 + N_FULL + 5 * (2 + 4 + 7) + 1 + 35;
struct Item { int type, mb, nt, k0, k1, nsplit; };
__device__ __forceinline__ Item get_item(int i) {
  Item t;
  if (i < N_G1) { t.type = 0; t.mb = i / 12; t.nt = i % 12; t.k0 = 0; t.k1 = 10; t.nsplit = 1; return t; }
  i -= N_G1; t.type = 1; t.nt = i % 5;
  if (i < 20) { t.mb = SB0 + i / 5; t.k0 = 0; t.k1 = 24; t.nsplit = t.mb == 12 ? 3 : t.mb == 13 ? 5 : 8; return t; }
  i -= 20;
  if (i < N_FULL) { t.mb = i / 5; t.k0 = 0; t.k1 = 120; t.nsplit = 1; return t; }
  i -= N_FULL;
  int ns;
  if (i < 10) { t.mb = 12; ns = 2; } else if (i < 30) { i -= 10; t.mb = 13; ns = 4; } else if (i < 65) { i -= 30; t.mb = 14; ns = 7; }
  else if (i == 65) { t.type = 2; t.mb = t.k0 = t.k1 = 0; t.nsplit = 1; return t; }
  else { i -= 66; t.mb = 15; ns = 7; }
  t.nt = i % 5;
  const int p = i / 5;
  t.k0 = 24 + (96 * p) / ns; t.k1 = 24 + (96 * (p + 1)) / ns; t.nsplit = ns + 1;
  return t;
}
__device__ __forceinline__ void store_tile(const uint32_t* p, uint32_t stg, const CUtensorMap* tm, int c0, int r0, int wg, int t128) {
  const int lane = t128 & 31, r = (t128 >> 5) * 16 + (lane & 15);
  if (t128 == 0) asm volatile("cp.async.bulk.wait_group.read 0;" ::: "memory");
  bar_sync(1 + wg, 128);
#pragma unroll
  for (int j = 0; j < 8; j++) {
    const int c = 2 * j + (lane >> 4);
    const uint32_t a = stg + (c >> 3) * 8192 + r * 128 + (((c & 7) ^ (r & 7)) << 4);
    asm volatile("stmatrix.sync.aligned.m8n8.x4.shared.b16 [%0], {%1,%2,%3,%4};" :: "r"(a), "r"(p[4 * j]), "r"(p[4 * j + 1]), "r"(p[4 * j + 2]), "r"(p[4 * j + 3]) : "memory");
  }
  fence_async();
  bar_sync(1 + wg, 128);
  if (t128 == 0) {
    asm volatile("cp.async.bulk.tensor.2d.global.shared::cta.bulk_group [%0, {%2, %3}], [%1];" :: "l"(tm), "r"(stg), "r"(c0), "r"(r0) : "memory");
    asm volatile("cp.async.bulk.tensor.2d.global.shared::cta.bulk_group [%0, {%2, %3}], [%1];" :: "l"(tm), "r"(stg + 8192), "r"(c0 + 64), "r"(r0) : "memory");
    asm volatile("cp.async.bulk.commit_group;" ::: "memory");
  }
}
}
__global__ void __launch_bounds__(384, 1)
helper_kernel(const __grid_constant__ CUtensorMap tm_x, const __grid_constant__ CUtensorMap tm_g, const __grid_constant__ CUtensorMap tm_u,
              const __grid_constant__ CUtensorMap tm_h, const __grid_constant__ CUtensorMap tm_o, const __grid_constant__ CUtensorMap tm_wd,
              const __grid_constant__ CUtensorMap tm_wo, const __grid_constant__ CUtensorMap tm_hs, const __grid_constant__ CUtensorMap tm_out,
              const bf16* __restrict__ x) {
  using namespace hk;
  extern __shared__ __align__(1024) unsigned char smem[];
  const uint32_t sb = smem_u32(smem), bar = sb + OFF_BAR;
  const int tid = threadIdx.x, lane = tid & 31, wg = __shfl_sync(~0u, tid >> 7, 0);
  if (tid == 0) { for (int i = 0; i < STAGES; i++) { mbar_init(bar + 8 * i, 1); mbar_init(bar + 64 + 8 * i, 2); } asm volatile("fence.mbarrier_init.release.cluster;" ::: "memory"); }
  __syncthreads();
  const int i0 = blockIdx.x;
  if (wg == 2) {
    asm volatile("setmaxnreg.dec.sync.aligned.u32 40;");
    if (tid == 256) {
      uint32_t it = 0;
      wait_flag(&g_flag[F_LN], 96);
      wait_flag(&g_flag[F_W], 48);
      for (int i = i0; i < N_ITEMS; i += NCTA) {
        const Item t = get_item(i);
        const int m0 = t.mb * 128, n0 = t.nt * 128;
        int kb = t.k0;
        if (t.type == 1 && kb == 0) wait_flag(&g_flag[16 + t.mb], 24);
        for (; kb < t.k1 && kb < 24; kb++, it++) {
          const uint32_t st = it % STAGES, base = sb + st * STAGE, full = bar + 8 * st;
          mbar_wait_long(bar + 64 + 8 * st, ((it / STAGES) & 1) ^ 1);
          if (t.type == 0) {
            mbar_expect(full, 49152);
            tma2d(base, &tm_x, kb * 64, m0, full);
            tma2d(base + 16384, &tm_g, n0, kb * 64, full);
            tma2d(base + 24576, &tm_g, n0 + 64, kb * 64, full);
            tma2d(base + 32768, &tm_u, n0, kb * 64, full);
            tma2d(base + 40960, &tm_u, n0 + 64, kb * 64, full);
          } else {
            mbar_expect(full, 32768);
            tma2d(base, &tm_h, kb * 64, m0, full);
            tma2d(base + 16384, &tm_wd, n0, kb * 64, full);
            tma2d(base + 24576, &tm_wd, n0 + 64, kb * 64, full);
          }
        }
        const int kf = kb;
        for (; kb < t.k1; kb++, it++) {
          const uint32_t st = it % STAGES, base = sb + st * STAGE, full = bar + 8 * st;
          const int k0 = (kb - 24) * 64;
          mbar_wait_long(bar + 64 + 8 * st, ((it / STAGES) & 1) ^ 1);
          mbar_expect(full, 32768);
          tma2d(base + 16384, &tm_wo, n0, k0, full);
          tma2d(base + 24576, &tm_wo, n0 + 64, k0, full);
          if (kb == kf + STAGES - 2) {
            wait_flag(&g_flag[t.mb], 96);
            for (int j = STAGES - 2; j > 0; j--) tma3d(sb + ((it - j) % STAGES) * STAGE, &tm_o, 0, k0 - j * 64, m0 / 32, bar + 8 * ((it - j) % STAGES));
          }
          if (kb >= kf + STAGES - 2) tma3d(base, &tm_o, 0, k0, m0 / 32, full);
        }
      }
    }
  } else {
    asm volatile("setmaxnreg.inc.sync.aligned.u32 232;");
    uint32_t it = 0;
    for (int i = i0; i < N_ITEMS; i += NCTA) {
      const Item t = get_item(i);
      const int row = t.mb * 128 + wg * 64 + ((tid >> 5) & 3) * 16 + (lane >> 2);
      if (t.type == 2) continue;
      if (t.type == 0) {
        float dg[64], du[64];
#pragma unroll
        for (int j = 0; j < 64; j++) { dg[j] = 0.f; du[j] = 0.f; }
        for (int kb = 0; kb < 10; kb++, it++) {
          const uint32_t st = it % STAGES, base = sb + st * STAGE;
          mbar_wait_long(bar + 8 * st, (it / STAGES) & 1);
          const uint64_t da = mkdesc(base + wg * 8192, 16, 1024, 1), db = mkdesc(base + 16384, 8192, 1024, 1);
          WG_FENCE();
#pragma unroll
          for (int k = 0; k < 4; k++) { wg_ss128<0>(dg, da + 2 * k, db + 128 * k); wg_ss128<0>(du, da + 2 * k, db + 1024 + 128 * k); }
          WG_COMMIT();
          WG_WAIT(1);
          if (kb > 0 && (tid & 127) == 0) mbar_arrive(bar + 64 + 8 * ((it - 1) % STAGES));
        }
        WG_WAIT(0);
        if ((tid & 127) == 0) mbar_arrive(bar + 64 + 8 * ((it - 1) % STAGES));
        uint32_t p[32];
#pragma unroll
        for (int j = 0; j < 32; j++) p[j] = pack2(bfr(dg[2 * j]) * bfr(du[2 * j]), bfr(dg[2 * j + 1]) * bfr(du[2 * j + 1]));
        store_tile(p, sb + OFF_ST + wg * 16384, &tm_hs, t.nt * 128, t.mb * 128 + wg * 64, wg, tid & 127);
        if ((tid & 127) == 0) {
          asm volatile("cp.async.bulk.wait_group 0;" ::: "memory");
          asm volatile("fence.proxy.async;" ::: "memory");
          __threadfence(); atomicAdd(&g_flag[16 + t.mb], 1u);
        }
      } else {
        float d[64];
#pragma unroll
        for (int j = 0; j < 64; j++) d[j] = 0.f;
        uint32_t xr[32];
        {
          const uint32_t* xi = reinterpret_cast<const uint32_t*>(x + (size_t)row * DM + t.nt * 128 + (lane & 3) * 2);
#pragma unroll
          for (int j = 0; j < 16; j++) { xr[2 * j] = __ldg(xi + j * 4); xr[2 * j + 1] = __ldg(xi + j * 4 + 4 * DM); }
        }
        int kb = t.k0;
        for (; kb < t.k1 && kb < 24; kb++, it++) {
          const uint32_t st = it % STAGES, base = sb + st * STAGE;
          mbar_wait_long(bar + 8 * st, (it / STAGES) & 1);
          const uint64_t da = mkdesc(base + wg * 8192, 16, 1024, 1), db = mkdesc(base + 16384, 8192, 1024, 1);
          WG_FENCE();
#pragma unroll
          for (int k = 0; k < 4; k++) wg_ss128<0>(d, da + 2 * k, db + 128 * k);
          WG_COMMIT();
          WG_WAIT(1);
          if (kb > t.k0 && (tid & 127) == 0) mbar_arrive(bar + 64 + 8 * ((it - 1) % STAGES));
        }
        WG_WAIT(0);
        for (; kb < t.k1; kb++, it++) {
          const uint32_t st = it % STAGES, base = sb + st * STAGE;
          mbar_wait_long(bar + 8 * st, (it / STAGES) & 1);
          const uint64_t da = mkdesc(base + wg * 8192, 4096, 512, 2), db = mkdesc(base + 16384, 8192, 1024, 1);
          WG_FENCE();
#pragma unroll
          for (int k = 0; k < 4; k++) wg_ss128<1>(d, da + 64 * k, db + 128 * k);
          WG_COMMIT();
          WG_WAIT(1);
          if (kb > t.k0 && (tid & 127) == 0) mbar_arrive(bar + 64 + 8 * ((it - 1) % STAGES));
        }
        WG_WAIT(0);
        if ((tid & 127) == 0) mbar_arrive(bar + 64 + 8 * ((it - 1) % STAGES));
        {
          const uint32_t m = t.k0 == 0 ? 0xffff0000u : 0u;
#pragma unroll
          for (int j = 0; j < 32; j++) { d[2 * j] += __uint_as_float((xr[j] << 16) & m); d[2 * j + 1] += __uint_as_float(xr[j] & m); }
        }
        bool fin = true;
        if (t.nsplit > 1) {
          const int ti = (t.mb - SB0) * 5 + t.nt;
          float4* pp = g_part + ti * 4096 + tid;
#pragma unroll
          for (int j = 0; j < 16; j++) red4(pp + j * 256, d[4 * j], d[4 * j + 1], d[4 * j + 2], d[4 * j + 3]);
          bar_sync(1 + wg, 128);
          volatile unsigned* sflag = reinterpret_cast<volatile unsigned*>(smem + OFF_BAR + 256 + wg * 4);
          if ((tid & 127) == 0) {
            __threadfence();
            const unsigned old = atomicAdd(&g_flag[32 + ti], wg ? 0x10000u : 1u);
            *sflag = ((wg ? old >> 16 : old & 0xffffu) == (unsigned)t.nsplit - 1);
            __threadfence();
          }
          bar_sync(1 + wg, 128);
          fin = __shfl_sync(~0u, *sflag, 0) != 0;
          if (fin) {
#pragma unroll
            for (int j = 0; j < 16; j++) {
              const float4 u = __ldcg(pp + j * 256);
              d[4 * j] = u.x; d[4 * j + 1] = u.y; d[4 * j + 2] = u.z; d[4 * j + 3] = u.w;
            }
          }
        }
        if (fin) {
          uint32_t p[32];
#pragma unroll
          for (int j = 0; j < 32; j++) p[j] = pack2(d[2 * j], d[2 * j + 1]);
          store_tile(p, sb + OFF_ST + wg * 16384, &tm_out, t.nt * 128, t.mb * 128 + wg * 64, wg, tid & 127);
        }
      }
    }
    bar_sync(3, 256);
    if (tid >= 32 && tid < 64) {
      asm volatile("griddepcontrol.wait;" ::: "memory");
      unsigned old = 0;
      if (lane == 0) old = atomicAdd(&g_flag[F_DONE], 1u);
      if (__shfl_sync(~0u, old, 0) == NCTA - 1) { g_flag[lane] = 0; g_flag[32 + lane] = 0; }
    }
    if ((tid & 127) == 0) asm volatile("cp.async.bulk.wait_group 0;" ::: "memory");
  }
}

__global__ void fb_ln(const bf16* __restrict__ x) {
  uint2 u[5];
  const int row = blockIdx.x * 8 + (threadIdx.x >> 5), lane = threadIdx.x & 31;
  for (int j = 0; j < 5; j++) u[j] = reinterpret_cast<const uint2*>(x + (size_t)row * DM)[j * 32 + lane];
  ln_row(u, row, lane);
}
__global__ void fb_gemm(const bf16* A0, const bf16* A1, int m_split, const bf16* B, bf16* C0, bf16* C1, int N, int K, int mode, const bf16* R0, const bf16* R1) {
  const int n = blockIdx.x * blockDim.x + threadIdx.x, m = blockIdx.y;
  const bf16* a = m < m_split ? A0 + (size_t)m * K : A1 + (size_t)(m - m_split) * K;
  bf16* c = (m < m_split ? C0 + (size_t)m * N : C1 + (size_t)(m - m_split) * N) + n;
  float acc = 0.f;
  for (int k = 0; k < K; k++) acc += __bfloat162float(a[k]) * __bfloat162float(B[(size_t)k * N + n]);
  if (mode == 1) acc = bfr(acc) * __bfloat162float(*c);
  if (mode == 2) acc += __bfloat162float(R0[(size_t)m * N + n]) + __bfloat162float(R1[(size_t)m * N + n]);
  *c = __float2bfloat16_rn(acc);
}
__global__ void fb_attn(const bf16* q, const bf16* k, const bf16* v, bf16* o) {
  const int h = blockIdx.x, r = blockIdx.y, t = threadIdx.x;
  __shared__ float p[40];
  if (t < 40) {
    float a = 0.f;
    for (int e = 0; e < 192; e++) a += __bfloat162float(q[r * HD + h * 192 + e]) * __bfloat162float(k[t * HD + h * 192 + e]);
    p[t] = (r < 8 || r >= t) ? a * 0.07216878364870322f : -INFINITY;
  }
  __syncthreads();
  float mx = p[0], sum = 0.f, a = 0.f;
  for (int i = 1; i < 40; i++) mx = fmaxf(mx, p[i]);
  for (int i = 0; i < 40; i++) sum += __expf(p[i] - mx);
  for (int i = 0; i < 40; i++) a += bfr(__expf(p[i] - mx) / sum) * __bfloat162float(v[i * HD + h * 192 + t]);
  o[r * HD + h * 192 + t] = __float2bfloat16_rn(a);
}

typedef CUresult (*EncodeFn)(CUtensorMap*, CUtensorMapDataType, cuuint32_t, void*, const cuuint64_t*, const cuuint64_t*, const cuuint32_t*,
                             const cuuint32_t*, CUtensorMapInterleave, CUtensorMapSwizzle, CUtensorMapL2promotion, CUtensorMapFloatOOBfill);
static void make_map(EncodeFn enc, CUtensorMap* m, const void* p, int rank, const cuuint64_t* dims, const cuuint64_t* strides,
                     const cuuint32_t* box, CUtensorMapSwizzle swz) {
  cuuint32_t es[3] = {1, 1, 1};
  enc(m, CU_TENSOR_MAP_DATA_TYPE_BFLOAT16, rank, const_cast<void*>(p), dims, strides, box, es, CU_TENSOR_MAP_INTERLEAVE_NONE, swz,
      CU_TENSOR_MAP_L2_PROMOTION_L2_128B, CU_TENSOR_MAP_FLOAT_OOB_FILL_NONE);
}
static void map2d(EncodeFn enc, CUtensorMap* m, const void* p, int cols, int rows, int bc, int br, CUtensorMapSwizzle swz) {
  cuuint64_t dims[2] = {(cuuint64_t)cols, (cuuint64_t)rows}, strides[1] = {(cuuint64_t)cols * 2};
  cuuint32_t box[2] = {(cuuint32_t)bc, (cuuint32_t)br};
  make_map(enc, m, p, 2, dims, strides, box, swz);
}

extern "C" void kernel_launch(void* const* d_in, const int* in_sizes, int n_in, void* d_out, int out_size) {
  const bf16* x = (const bf16*)d_in[0];
  const bf16* mem0 = (const bf16*)d_in[1];
  const bf16* Wq = (const bf16*)d_in[2];
  const bf16* Wk = (const bf16*)d_in[3];
  const bf16* Wv = (const bf16*)d_in[4];
  const bf16* Wo = (const bf16*)d_in[5];
  const bf16* Wg = (const bf16*)d_in[8];
  const bf16* Wu = (const bf16*)d_in[9];
  const bf16* Wd = (const bf16*)d_in[10];
  bf16* out = (bf16*)d_out;

  void* fn = nullptr; cudaDriverEntryPointQueryResult qr;
  cudaGetDriverEntryPoint("cuTensorMapEncodeTiled", &fn, cudaEnableDefault, &qr);
  EncodeFn enc = (EncodeFn)fn;
  void *p_xn, *p_oT, *p_h;
  cudaGetSymbolAddress(&p_xn, g_xn); cudaGetSymbolAddress(&p_oT, g_oT); cudaGetSymbolAddress(&p_h, g_h);

  CUtensorMap t_x32, t_wv, t_wo16, t_x128, t_wg, t_wu, t_h, t_o, t_wd, t_wo64, t_hs, t_out, t_wq, t_wk;
  map2d(enc, &t_wq, Wq, HD, DM, 64, 128, CU_TENSOR_MAP_SWIZZLE_128B);
  map2d(enc, &t_wk, Wk, HD, DM, 64, 128, CU_TENSOR_MAP_SWIZZLE_128B);
  map2d(enc, &t_hs, p_h, FF, SEQ, 64, 64, CU_TENSOR_MAP_SWIZZLE_128B);
  map2d(enc, &t_out, out, DM, SEQ, 64, 64, CU_TENSOR_MAP_SWIZZLE_128B);
  map2d(enc, &t_x32, p_xn, DM, SEQ, 64, 32, CU_TENSOR_MAP_SWIZZLE_128B);
  map2d(enc, &t_wv, Wv, HD, DM, 64, 128, CU_TENSOR_MAP_SWIZZLE_128B);
  map2d(enc, &t_wo16, Wo, DM, HD, 16, 64, CU_TENSOR_MAP_SWIZZLE_32B);
  map2d(enc, &t_x128, p_xn, DM, SEQ, 64, 128, CU_TENSOR_MAP_SWIZZLE_128B);
  map2d(enc, &t_wg, Wg, FF, DM, 64, 64, CU_TENSOR_MAP_SWIZZLE_128B);
  map2d(enc, &t_wu, Wu, FF, DM, 64, 64, CU_TENSOR_MAP_SWIZZLE_128B);
  map2d(enc, &t_h, p_h, FF, SEQ, 64, 128, CU_TENSOR_MAP_SWIZZLE_128B);
  map2d(enc, &t_wd, Wd, DM, FF, 64, 64, CU_TENSOR_MAP_SWIZZLE_128B);
  map2d(enc, &t_wo64, Wo, DM, HD, 64, 64, CU_TENSOR_MAP_SWIZZLE_128B);
  {
    cuuint64_t dims[3] = {32, (cuuint64_t)HD, (cuuint64_t)NSEG}, strides[2] = {64, (cuuint64_t)HD * 64};
    cuuint32_t box[3] = {32, 64, 4};
    make_map(enc, &t_o, p_oT, 3, dims, strides, box, CU_TENSOR_MAP_SWIZZLE_64B);
  }
  cudaFuncSetAttribute(chain_kernel, cudaFuncAttributeMaxDynamicSharedMemorySize, ck::SMEM);
  cudaFuncSetAttribute(helper_kernel, cudaFuncAttributeMaxDynamicSharedMemorySize, hk::SMEM);

  cudaStream_t st = cudaStreamPerThread;
  {
    cudaLaunchConfig_t cfg = {};
    cfg.gridDim = dim3(ck::CL * ck::NCL); cfg.blockDim = dim3(384); cfg.dynamicSmemBytes = ck::SMEM; cfg.stream = st;
    cudaLaunchAttribute at[1];
    at[0].id = cudaLaunchAttributeClusterDimension; at[0].val.clusterDim.x = ck::CL; at[0].val.clusterDim.y = 1; at[0].val.clusterDim.z = 1;
    cfg.attrs = at; cfg.numAttrs = 1;
    int ncl = 0;
    if (cudaOccupancyMaxActiveClusters(&ncl, chain_kernel, &cfg) != cudaSuccess) { (void)cudaGetLastError(); ncl = 0; }
    if (ncl < ck::NCL) {
      bf16 *xn = (bf16*)p_xn, *h = (bf16*)p_h, *q = (bf16*)p_oT, *k = q + 40 * HD, *v = k + 40 * HD, *o = v + 40 * HD, *mem = o + 40 * HD, *att = mem + 8 * DM;
      fb_ln<<<SEQ / 8, 256, 0, st>>>(x);
      for (int s = 0; s < NSEG; s++) {
        const bf16 *m = s ? mem : mem0, *xs = xn + s * 32 * DM;
        fb_gemm<<<dim3(HD / 128, 40), 128, 0, st>>>(m, xs, 8, Wq, q, q + 8 * HD, HD, DM, 0, nullptr, nullptr);
        fb_gemm<<<dim3(HD / 128, 40), 128, 0, st>>>(m, xs, 8, Wk, k, k + 8 * HD, HD, DM, 0, nullptr, nullptr);
        fb_gemm<<<dim3(HD / 128, 40), 128, 0, st>>>(m, xs, 8, Wv, v, v + 8 * HD, HD, DM, 0, nullptr, nullptr);
        fb_attn<<<dim3(32, 40), 192, 0, st>>>(q, k, v, o);
        fb_gemm<<<dim3(DM / 128, 40), 128, 0, st>>>(o, o + 8 * HD, 8, Wo, mem, att + s * 32 * DM, DM, HD, 0, nullptr, nullptr);
      }
      fb_gemm<<<dim3(FF / 128, SEQ), 128, 0, st>>>(xn, xn, SEQ, Wg, h, h, FF, DM, 0, nullptr, nullptr);
      fb_gemm<<<dim3(FF / 128, SEQ), 128, 0, st>>>(xn, xn, SEQ, Wu, h, h, FF, DM, 1, nullptr, nullptr);
      fb_gemm<<<dim3(DM / 128, SEQ), 128, 0, st>>>(h, h, SEQ, Wd, out, out, DM, FF, 2, x, att);
      return;
    }
    cudaLaunchKernelEx(&cfg, chain_kernel, t_x32, t_wv, t_wo16, t_wq, t_wk, mem0, x, 0u);
  }
  {
    cudaLaunchConfig_t cfg = {};
    cfg.gridDim = dim3(hk::NCTA); cfg.blockDim = dim3(384); cfg.dynamicSmemBytes = hk::SMEM; cfg.stream = st;
    cudaLaunchAttribute at[1];
    at[0].id = cudaLaunchAttributeProgrammaticStreamSerialization; at[0].val.programmaticStreamSerializationAllowed = 1;
    cfg.attrs = at; cfg.numAttrs = 1;
    cudaLaunchKernelEx(&cfg, helper_kernel, t_x128, t_wg, t_wu, t_h, t_o, t_wd, t_wo64, t_hs, t_out, x);
  }
}
```
